```python
import torch

def _softmax(x, axis=-1):
    return torch.softmax(x, dim=axis)
def _gelu(x):
    return torch.nn.functional.gelu(x, approximate="tanh")
def _silu(x):
    return torch.nn.functional.silu(x)
def _sigmoid(x):
    return torch.sigmoid(x)
def _layernorm(x, axis=-1, eps=1e-5):
    m = x.mean(dim=axis, keepdim=True)
    v = x.var(dim=axis, keepdim=True, unbiased=False)
    return (x - m) / torch.sqrt(v + eps)
def _scatter_add(tgt, idx, src, axis=0):
    return tgt.clone().index_add_(axis, idx, src)
def _segment_sum(src, seg, n):
    out = torch.zeros((n,) + src.shape[1:], dtype=src.dtype)
    return out.index_add_(0, seg, src)
def _pad(x, pw):
    flat = tuple(v for pair in reversed(pw) for v in pair)
    return torch.nn.functional.pad(x, flat)

kernel_name = 'standalone__deep_cross_xdeepfm__recsys'

def setup_inputs():

    _w = (lambda a: (lambda t: t.to(torch.bfloat16) if t.is_floating_point() else t)(torch.as_tensor(a)))
    B, F, D, L = 4096, 26, 64, 3
    V = min(1000000, 100000)
    Din = F * D
    return {
        "idx": _w((lambda lo, hi, *s: torch.randint(lo, hi, s))(0, V, B, F).to(torch.int64)),
        "table": _w((lambda *s: torch.randn(*s, dtype=torch.bfloat16) * 0.8)(V, D)),
        "ws_cin": _w((lambda *s: torch.randn(*s, dtype=torch.bfloat16) * 0.2)(L, F, F, F) * (1.0 / F)),
        "w_cin_out": _w((lambda *s: torch.randn(*s, dtype=torch.bfloat16) * 0.2)(L * F) * ((L * F) ** -0.5)),
        "w_dnn1": _w((lambda *s: torch.randn(*s, dtype=torch.bfloat16) * 0.8)(Din, Din) * (Din ** -0.5)),
        "b_dnn1": _w((lambda *s: torch.randn(*s, dtype=torch.bfloat16) * 1.6)(Din) * 0.1),
        "w_dnn2": _w((lambda *s: torch.randn(*s, dtype=torch.bfloat16) * 0.2)(Din) * (Din ** -0.5)),
        "b_out": _w((lambda *s: torch.randn(*s, dtype=torch.bfloat16) * 0.2)(1)),
    }

def reference(idx, table, ws_cin, w_cin_out, w_dnn1, b_dnn1, w_dnn2, b_out):
    x0 = table[idx]
    B = x0.shape[0]
    L = ws_cin.shape[0]
    xk = x0
    pooled = []
    for l in range(L):
        xk = torch.einsum('bid,bjd,hij->bhd', xk, x0, ws_cin[l])
        pooled.append(xk.sum(axis=-1))
    p_plus = torch.stack(pooled, axis=1).reshape(B, -1)
    logit_cin = p_plus @ w_cin_out
    h = x0.reshape(B, -1)
    h = _gelu(h @ w_dnn1 + b_dnn1)
    logit_dnn = h @ w_dnn2
    return logit_cin + logit_dnn + b_out
```

```cpp
#include <cuda_runtime.h>
#include <cuda_bf16.h>
#include <cuda.h>
#include <stdint.h>

template <int TB = 1>
__device__ __forceinline__ void wgmma_ss_n256(float (&d)[96], float (&e)[32], uint64_t descA, uint64_t descB, int scaleD) {
  asm volatile("{\n.reg .pred p;\nsetp.ne.b32 p, %130, 0;\n"
      "wgmma.mma_async.sync.aligned.m64n256k16.f32.bf16.bf16 {"
      "%0, %1, %2, %3, %4, %5, %6, %7, %8, %9, %10, %11, %12, %13, %14, %15,"
      "%16, %17, %18, %19, %20, %21, %22, %23, %24, %25, %26, %27, %28, %29, %30, %31,"
      "%32, %33, %34, %35, %36, %37, %38, %39, %40, %41, %42, %43, %44, %45, %46, %47,"
      "%48, %49, %50, %51, %52, %53, %54, %55, %56, %57, %58, %59, %60, %61, %62, %63,"
      "%64, %65, %66, %67, %68, %69, %70, %71, %72, %73, %74, %75, %76, %77, %78, %79,"
      "%80, %81, %82, %83, %84, %85, %86, %87, %88, %89, %90, %91, %92, %93, %94, %95,"
      "%96, %97, %98, %99, %100, %101, %102, %103, %104, %105, %106, %107, %108, %109, %110, %111,"
      "%112, %113, %114, %115, %116, %117, %118, %119, %120, %121, %122, %123, %124, %125, %126, %127"
      "}, %128, %129, p, 1, 1, 0, %131;\n}\n"
      : "+f"(d[0]), "+f"(d[1]), "+f"(d[2]), "+f"(d[3]), "+f"(d[4]), "+f"(d[5]), "+f"(d[6]), "+f"(d[7]),
        "+f"(d[8]), "+f"(d[9]), "+f"(d[10]), "+f"(d[11]), "+f"(d[12]), "+f"(d[13]), "+f"(d[14]), "+f"(d[15]),
        "+f"(d[16]), "+f"(d[17]), "+f"(d[18]), "+f"(d[19]), "+f"(d[20]), "+f"(d[21]), "+f"(d[22]), "+f"(d[23]),
        "+f"(d[24]), "+f"(d[25]), "+f"(d[26]), "+f"(d[27]), "+f"(d[28]), "+f"(d[29]), "+f"(d[30]), "+f"(d[31]),
        "+f"(d[32]), "+f"(d[33]), "+f"(d[34]), "+f"(d[35]), "+f"(d[36]), "+f"(d[37]), "+f"(d[38]), "+f"(d[39]),
        "+f"(d[40]), "+f"(d[41]), "+f"(d[42]), "+f"(d[43]), "+f"(d[44]), "+f"(d[45]), "+f"(d[46]), "+f"(d[47]),
        "+f"(d[48]), "+f"(d[49]), "+f"(d[50]), "+f"(d[51]), "+f"(d[52]), "+f"(d[53]), "+f"(d[54]), "+f"(d[55]),
        "+f"(d[56]), "+f"(d[57]), "+f"(d[58]), "+f"(d[59]), "+f"(d[60]), "+f"(d[61]), "+f"(d[62]), "+f"(d[63]),
        "+f"(d[64]), "+f"(d[65]), "+f"(d[66]), "+f"(d[67]), "+f"(d[68]), "+f"(d[69]), "+f"(d[70]), "+f"(d[71]),
        "+f"(d[72]), "+f"(d[73]), "+f"(d[74]), "+f"(d[75]), "+f"(d[76]), "+f"(d[77]), "+f"(d[78]), "+f"(d[79]),
        "+f"(d[80]), "+f"(d[81]), "+f"(d[82]), "+f"(d[83]), "+f"(d[84]), "+f"(d[85]), "+f"(d[86]), "+f"(d[87]),
        "+f"(d[88]), "+f"(d[89]), "+f"(d[90]), "+f"(d[91]), "+f"(d[92]), "+f"(d[93]), "+f"(d[94]), "+f"(d[95]),
        "+f"(e[0]), "+f"(e[1]), "+f"(e[2]), "+f"(e[3]), "+f"(e[4]), "+f"(e[5]), "+f"(e[6]), "+f"(e[7]),
        "+f"(e[8]), "+f"(e[9]), "+f"(e[10]), "+f"(e[11]), "+f"(e[12]), "+f"(e[13]), "+f"(e[14]), "+f"(e[15]),
        "+f"(e[16]), "+f"(e[17]), "+f"(e[18]), "+f"(e[19]), "+f"(e[20]), "+f"(e[21]), "+f"(e[22]), "+f"(e[23]),
        "+f"(e[24]), "+f"(e[25]), "+f"(e[26]), "+f"(e[27]), "+f"(e[28]), "+f"(e[29]), "+f"(e[30]), "+f"(e[31])
      : "l"(descA), "l"(descB), "r"(scaleD), "n"(TB));
}
template <int TB = 1>
__device__ __forceinline__ void wgmma_ss_n192(float (&d)[96], uint64_t descA, uint64_t descB, int scaleD) {
  asm volatile("{\n.reg .pred p;\nsetp.ne.b32 p, %98, 0;\n"
      "wgmma.mma_async.sync.aligned.m64n192k16.f32.bf16.bf16 {"
      "%0, %1, %2, %3, %4, %5, %6, %7, %8, %9, %10, %11, %12, %13, %14, %15,"
      "%16, %17, %18, %19, %20, %21, %22, %23, %24, %25, %26, %27, %28, %29, %30, %31,"
      "%32, %33, %34, %35, %36, %37, %38, %39, %40, %41, %42, %43, %44, %45, %46, %47,"
      "%48, %49, %50, %51, %52, %53, %54, %55, %56, %57, %58, %59, %60, %61, %62, %63,"
      "%64, %65, %66, %67, %68, %69, %70, %71, %72, %73, %74, %75, %76, %77, %78, %79,"
      "%80, %81, %82, %83, %84, %85, %86, %87, %88, %89, %90, %91, %92, %93, %94, %95"
      "}, %96, %97, p, 1, 1, 0, %99;\n}\n"
      : "+f"(d[0]), "+f"(d[1]), "+f"(d[2]), "+f"(d[3]), "+f"(d[4]), "+f"(d[5]), "+f"(d[6]), "+f"(d[7]),
        "+f"(d[8]), "+f"(d[9]), "+f"(d[10]), "+f"(d[11]), "+f"(d[12]), "+f"(d[13]), "+f"(d[14]), "+f"(d[15]),
        "+f"(d[16]), "+f"(d[17]), "+f"(d[18]), "+f"(d[19]), "+f"(d[20]), "+f"(d[21]), "+f"(d[22]), "+f"(d[23]),
        "+f"(d[24]), "+f"(d[25]), "+f"(d[26]), "+f"(d[27]), "+f"(d[28]), "+f"(d[29]), "+f"(d[30]), "+f"(d[31]),
        "+f"(d[32]), "+f"(d[33]), "+f"(d[34]), "+f"(d[35]), "+f"(d[36]), "+f"(d[37]), "+f"(d[38]), "+f"(d[39]),
        "+f"(d[40]), "+f"(d[41]), "+f"(d[42]), "+f"(d[43]), "+f"(d[44]), "+f"(d[45]), "+f"(d[46]), "+f"(d[47]),
        "+f"(d[48]), "+f"(d[49]), "+f"(d[50]), "+f"(d[51]), "+f"(d[52]), "+f"(d[53]), "+f"(d[54]), "+f"(d[55]),
        "+f"(d[56]), "+f"(d[57]), "+f"(d[58]), "+f"(d[59]), "+f"(d[60]), "+f"(d[61]), "+f"(d[62]), "+f"(d[63]),
        "+f"(d[64]), "+f"(d[65]), "+f"(d[66]), "+f"(d[67]), "+f"(d[68]), "+f"(d[69]), "+f"(d[70]), "+f"(d[71]),
        "+f"(d[72]), "+f"(d[73]), "+f"(d[74]), "+f"(d[75]), "+f"(d[76]), "+f"(d[77]), "+f"(d[78]), "+f"(d[79]),
        "+f"(d[80]), "+f"(d[81]), "+f"(d[82]), "+f"(d[83]), "+f"(d[84]), "+f"(d[85]), "+f"(d[86]), "+f"(d[87]),
        "+f"(d[88]), "+f"(d[89]), "+f"(d[90]), "+f"(d[91]), "+f"(d[92]), "+f"(d[93]), "+f"(d[94]), "+f"(d[95])
      : "l"(descA), "l"(descB), "r"(scaleD), "n"(TB));
}
template <unsigned long long DESC, int SCALE>
__device__ __forceinline__ void wgmma_rs_n56(float (&d)[28], uint32_t a0, uint32_t a1, uint32_t a2, uint32_t a3) {
  asm volatile("{\n.reg .b64 desc;\nmov.b64 desc, %32;\n"
      "wgmma.mma_async.sync.aligned.m64n56k16.f32.bf16.bf16 {"
      "%0, %1, %2, %3, %4, %5, %6, %7, %8, %9, %10, %11, %12, %13, %14, %15,"
      "%16, %17, %18, %19, %20, %21, %22, %23, %24, %25, %26, %27"
      "}, {%28, %29, %30, %31}, desc, %33, 1, 1, 0;\n}\n"
      : "+f"(d[0]), "+f"(d[1]), "+f"(d[2]), "+f"(d[3]), "+f"(d[4]), "+f"(d[5]), "+f"(d[6]), "+f"(d[7]),
        "+f"(d[8]), "+f"(d[9]), "+f"(d[10]), "+f"(d[11]), "+f"(d[12]), "+f"(d[13]), "+f"(d[14]), "+f"(d[15]),
        "+f"(d[16]), "+f"(d[17]), "+f"(d[18]), "+f"(d[19]), "+f"(d[20]), "+f"(d[21]), "+f"(d[22]), "+f"(d[23]),
        "+f"(d[24]), "+f"(d[25]), "+f"(d[26]), "+f"(d[27])
      : "r"(a0), "r"(a1), "r"(a2), "r"(a3), "n"(DESC), "n"(SCALE));
}
template <unsigned long long DESC, int SCALE>
__device__ __forceinline__ void wgmma_rs_n32(float (&d)[28], uint32_t a0, uint32_t a1, uint32_t a2, uint32_t a3) {
  asm volatile("{\n.reg .b64 desc;\nmov.b64 desc, %20;\n"
      "wgmma.mma_async.sync.aligned.m64n32k16.f32.bf16.bf16 {"
      "%0, %1, %2, %3, %4, %5, %6, %7, %8, %9, %10, %11, %12, %13, %14, %15"
      "}, {%16, %17, %18, %19}, desc, %21, 1, 1, 0;\n}\n"
      : "+f"(d[0]), "+f"(d[1]), "+f"(d[2]), "+f"(d[3]), "+f"(d[4]), "+f"(d[5]), "+f"(d[6]), "+f"(d[7]),
        "+f"(d[8]), "+f"(d[9]), "+f"(d[10]), "+f"(d[11]), "+f"(d[12]), "+f"(d[13]), "+f"(d[14]), "+f"(d[15])
      : "r"(a0), "r"(a1), "r"(a2), "r"(a3), "n"(DESC), "n"(SCALE));
}

constexpr int NB = 4096, NF = 26, DIN = 1664;
constexpr int NGEMM = 128, NEXTRA = 4, GRID = NGEMM + NEXTRA;
constexpr int NC_EXTRA = 84;
constexpr int NC_WG0 = 16;
constexpr int HK = 3;
constexpr int PE0 = 9;
constexpr int WD = 2;
constexpr int GI = 3;
constexpr int PE1 = 4;
constexpr int PE2 = 8;
constexpr int PS2 = 8;
constexpr int PS = 4;
constexpr int RB = 4;
constexpr int NC_GEMM = 29, NBIG = NB - NGEMM * NC_GEMM - NEXTRA * NC_EXTRA;
static_assert(NBIG >= 0 && NBIG <= NGEMM && NC_EXTRA % 2 == 0 && NC_EXTRA <= 92 && NC_WG0 <= 17 && NC_WG0 >= 15, "split");
constexpr int CW_MAIN = 22 * 1792, CW_LIN = 2 * 1024, CW_BYTES = CW_MAIN + CW_LIN;
constexpr int XSLOT = 4096;

constexpr int UNIT = 8192, FS = 18;
constexpr int U_W = 6, U_XB = 18, U_SP = 24;
constexpr int CW_CUT = 9;
constexpr int OFF_CW = 0, OFF_CW2 = 6 * UNIT, OFF_CWL = 9 * UNIT;
constexpr int OFF_PART = OFF_CWL + CW_LIN;
constexpr int CROW = 528;
constexpr int OFF_CIN = 2 * UNIT;
constexpr int OFF_GIDX = 26 * UNIT;
constexpr int OFF_TIDX = OFF_GIDX + 128 * NF * 4 - 8 * 64 * 4;
constexpr int OFF_CIDX = OFF_GIDX + 128 * NF * 4;
constexpr int OFF_EPI = OFF_CIDX + 30 * NF * 4;
constexpr int OFF_DNN = OFF_EPI + 128 * 16;
constexpr int OFF_BAR = OFF_DNN + 96 * 4;
constexpr int SMEM_BYTES = OFF_BAR + 66 * 8;
static_assert(CW_CUT * 1792 <= 2 * UNIT && (22 - CW_CUT) * 1792 <= 3 * UNIT && 30 * CROW <= 2 * UNIT, "smem");
constexpr uint32_t SMEM_BASE = 1024;
static_assert(SMEM_BYTES <= 232448, "smem");
static_assert(OFF_EPI % 16 == 0 && OFF_CIDX % 16 == 0 && OFF_BAR % 8 == 0, "align");
constexpr int XOFF_W3 = 0, XOFF_W2 = 35152, XOFF_W1 = 70304, XOFF_M = XOFF_W1 + 8 * 1352, XOFF_S = XOFF_M + 32 * 40 * 4,
              XOFF_SLOT = 10 * UNIT, XOFF_CIN0 = 2 * UNIT, XOFF_CIN1 = 18 * UNIT, XOFF_CIDX = 22 * UNIT;
static_assert(XOFF_S + 14 * 3136 <= 21 * UNIT && 46 * CROW <= 3 * UNIT, "smem");

constexpr int BAR_FULL = 8,
              BAR_EV = 16,
              BAR_CW = 24,
              BAR_GIDX = 25, BAR_CIDX = 26,
              BAR_W0 = 27,
              BAR_DNN = 28,
              BAR_T = 29,
              BAR_GDONE = 30,
              BAR_PART = 31,
              BAR_CFULL = 32,
              BAR_C0 = 64;
constexpr int EV_CW = 29, EV_CIN = 30, EV_SLOT = 31, EV_END = 33;
__device__ __forceinline__ uint32_t ev_bar(uint32_t bars, int e) { return bars + 8 * (BAR_EV + (e & 7)); }
__device__ __forceinline__ uint32_t ev_par(int e) { return (e >> 3) & 1; }
__host__ __device__ constexpr int b_x(int t) { return ((0xb2c1430bu >> (4 * t)) & 15) * 2; }
__host__ __device__ constexpr int b_w(int t) { return (0x0d0a120eu >> (8 * (t & 3))) & 31; }
__host__ __device__ constexpr int b_ws(int t) { return (t & 3) == 3 ? 4 : 1; }

struct Scratch {
  uint4 cw[CW_BYTES / 16];
  float part[8 * NB];
  unsigned dflag[16 * 8];
  unsigned epoch[GRID];
  unsigned foldflag;
};
__device__ __align__(128) Scratch g_scratch;
struct GPtr { Scratch* s; const uint4* tab; uint32_t zero; };

__device__ __forceinline__ void wg_fence() { asm volatile("wgmma.fence.sync.aligned;" ::: "memory"); }
__device__ __forceinline__ void wg_commit() { asm volatile("wgmma.commit_group.sync.aligned;" ::: "memory"); }
template <int N> __device__ __forceinline__ void wg_wait() { asm volatile("wgmma.wait_group.sync.aligned %0;" ::"n"(N) : "memory"); }
__device__ __forceinline__ uint64_t mkdesc(uint32_t addr, uint32_t lbo, uint32_t sbo, uint32_t swz) {
  return (uint64_t)((addr & 0x3FFFF) >> 4) | ((uint64_t)(lbo >> 4) << 16) | ((uint64_t)(sbo >> 4) << 32) | ((uint64_t)swz << 62);
}
__device__ __forceinline__ bool elect1() {
  uint32_t p; asm volatile("{\n.reg .pred p;\nelect.sync _|p, 0xffffffff;\nselp.b32 %0, 1, 0, p;\n}" : "=r"(p)); return p;
}
__device__ __forceinline__ int fresh(int v) { asm volatile("" : "+r"(v)); return v; }
__device__ __forceinline__ void mbar_init(uint32_t bar, uint32_t cnt) { asm volatile("mbarrier.init.shared::cta.b64 [%0], %1;" ::"r"(bar), "r"(cnt) : "memory"); }
__device__ __forceinline__ void mbar_arrive(uint32_t bar) { asm volatile("mbarrier.arrive.shared::cta.b64 _, [%0];" ::"r"(bar) : "memory"); }
__device__ __forceinline__ void mbar_arrive_cta(uint32_t bar, uint32_t cta) {
  asm volatile("{\n.reg .b32 r;\nmapa.shared::cluster.u32 r, %0, %1;\nmbarrier.arrive.shared::cluster.b64 _, [r];\n}" ::"r"(bar), "r"(cta) : "memory");
}
__device__ __forceinline__ void mbar_expect_tx(uint32_t bar, uint32_t bytes) { asm volatile("mbarrier.arrive.expect_tx.shared::cta.b64 _, [%0], %1;" ::"r"(bar), "r"(bytes) : "memory"); }
__device__ __forceinline__ void mbar_wait(uint32_t bar, uint32_t parity) {
  asm volatile("{\n.reg .pred p;\n.reg .u32 n;\n"
               "mbarrier.try_wait.parity.shared::cta.b64 p, [%0], %1;\n"
               "@p bra DONE;\n"
               "mov.u32 n, 0;\nLAB_WAIT:\n"
               "mbarrier.try_wait.parity.shared::cta.b64 p, [%0], %1;\n"
               "@p bra DONE;\n"
               "add.u32 n, n, 1;\n"
               "setp.lt.u32 p, n, 400000;\n"
               "@p bra LAB_WAIT;\n"
               "DONE:\n}" ::"r"(bar), "r"(parity) : "memory");
}
__device__ __forceinline__ void flag_wait(const unsigned* p, unsigned target, unsigned sleep_ns) {
  asm volatile("{\n.reg .pred p;\n.reg .u32 n, v;\nmov.u32 n, 0;\nLAB_WAIT:\n"
               "ld.acquire.gpu.global.u32 v, [%0];\n"
               "sub.u32 v, v, %1;\n"
               "setp.ge.s32 p, v, 0;\n"
               "@p bra DONE;\n"
               "nanosleep.u32 %2;\n"
               "add.u32 n, n, 1;\n"
               "setp.lt.u32 p, n, 400000;\n"
               "@p bra LAB_WAIT;\n"
               "DONE:\n}" ::"l"(p), "r"(target), "r"(sleep_ns) : "memory");
}
__device__ __forceinline__ void flag_add(unsigned* p) { asm volatile("red.release.gpu.global.add.u32 [%0], 1;" ::"l"(p) : "memory"); }
__device__ __forceinline__ void tma_load(uint32_t dst, const CUtensorMap* tm, int c0, int c1, uint32_t bar) {
  asm volatile("cp.async.bulk.tensor.2d.shared::cluster.global.mbarrier::complete_tx::bytes [%0], [%1, {%3, %4}], [%2];"
               ::"r"(dst), "l"(tm), "r"(bar), "r"(c0), "r"(c1) : "memory");
}
__device__ __forceinline__ void tma_row_mc(uint32_t dst, const CUtensorMap* tm, int row, uint32_t bar) {
  asm volatile("cp.async.bulk.tensor.2d.shared::cluster.global.mbarrier::complete_tx::bytes.multicast::cluster [%0], [%1, {%3, %4}], [%2], %5;"
               ::"r"(dst), "l"(tm), "r"(bar), "r"(0), "r"(row), "h"((uint16_t)3));
}
__device__ __forceinline__ void tma_row(uint32_t dst, const CUtensorMap* tm, int row, uint32_t bar) {
  asm volatile("cp.async.bulk.tensor.2d.shared::cluster.global.mbarrier::complete_tx::bytes [%0], [%1, {%3, %4}], [%2];"
               ::"r"(dst), "l"(tm), "r"(bar), "r"(0), "r"(row));
}
__device__ __forceinline__ void bulk_load(uint32_t dst, const void* src, uint32_t bytes, uint32_t bar) {
  asm volatile("cp.async.bulk.shared::cluster.global.mbarrier::complete_tx::bytes [%0], [%1], %2, [%3];"
               ::"r"(dst), "l"(src), "r"(bytes), "r"(bar));
}
__device__ __forceinline__ void l2_prefetch(const void* src, uint32_t bytes) {
  asm volatile("cp.async.bulk.prefetch.L2.global [%0], %1;" ::"l"(src), "r"(bytes));
}
__device__ __forceinline__ void w_prefetch(const __nv_bfloat16* w1, int f, int cta, int piece) {
  l2_prefetch(w1 + (f * 64 + (cta >> 3) * 4 + (cta & 1) * 2 + (piece & 1)) * DIN + (piece < 2 ? (cta & 6) * 192 : 1536 + (cta & 4) * 16),
              piece < 2 ? 768 : 128);
}
__device__ __forceinline__ void cpasync16(uint32_t dst, const void* src) {
  asm volatile("cp.async.cg.shared.global [%0], [%1], 16;" ::"r"(dst), "l"(src) : "memory");
}
template <int ID, int N> __device__ __forceinline__ void bar_sync() { asm volatile("bar.sync %0, %1;" ::"n"(ID), "n"(N) : "memory"); }
template <int ID, int N> __device__ __forceinline__ void bar_arrive() { asm volatile("bar.arrive %0, %1;" ::"n"(ID), "n"(N) : "memory"); }
__device__ __forceinline__ void ldsm4t(uint32_t& a, uint32_t& b, uint32_t& c, uint32_t& d, uint32_t addr) {
  asm volatile("ldmatrix.sync.aligned.m8n8.x4.trans.shared.b16 {%0,%1,%2,%3}, [%4];" : "=r"(a), "=r"(b), "=r"(c), "=r"(d) : "r"(addr) : "memory");
}
__device__ __forceinline__ int lds32(uint32_t addr) { int v; asm volatile("ld.shared.b32 %0, [%1];" : "=r"(v) : "r"(addr)); return v; }
__device__ __forceinline__ int2 lds64(uint32_t addr) { int2 v; asm volatile("ld.shared.v2.b32 {%0,%1}, [%2];" : "=r"(v.x), "=r"(v.y) : "r"(addr)); return v; }
__device__ __forceinline__ int4 lds128(uint32_t addr) {
  int4 v; asm volatile("ld.shared.v4.b32 {%0,%1,%2,%3}, [%4];" : "=r"(v.x), "=r"(v.y), "=r"(v.z), "=r"(v.w) : "r"(addr)); return v;
}
__device__ __forceinline__ float4 lds128f(uint32_t addr) {
  float4 v; asm volatile("ld.shared.v4.f32 {%0,%1,%2,%3}, [%4];" : "=f"(v.x), "=f"(v.y), "=f"(v.z), "=f"(v.w) : "r"(addr) : "memory"); return v;
}
__device__ __forceinline__ void sts32f(uint32_t addr, float v) { asm volatile("st.shared.f32 [%0], %1;" ::"r"(addr), "f"(v) : "memory"); }
__device__ __forceinline__ float bf_lo(uint32_t v) { return __uint_as_float(v << 16); }
__device__ __forceinline__ float bf_hi(uint32_t v) { return __uint_as_float(v & 0xffff0000u); }
__device__ __forceinline__ float bf2f(__nv_bfloat16 v) { return __bfloat162float(v); }

__device__ __forceinline__ uint32_t mul2(uint32_t a, uint32_t b) {
  uint32_t r; asm volatile("mul.rn.bf16x2 %0, %1, %2;" : "=r"(r) : "r"(a), "r"(b)); return r;
}
__device__ __forceinline__ uint32_t mul2lo(uint32_t a, uint32_t b) {
  uint32_t r;
  asm volatile("{\n.reg .b16 l, h;\n.reg .b32 t;\nmov.b32 {l, h}, %2;\nmov.b32 t, {l, l};\nmul.rn.bf16x2 %0, %1, t;\n}" : "=r"(r) : "r"(a), "r"(b));
  return r;
}
__device__ __forceinline__ uint32_t mul2hi(uint32_t a, uint32_t b) {
  uint32_t r;
  asm volatile("{\n.reg .b16 l, h;\n.reg .b32 t;\nmov.b32 {l, h}, %2;\nmov.b32 t, {h, h};\nmul.rn.bf16x2 %0, %1, t;\n}" : "=r"(r) : "r"(a), "r"(b));
  return r;
}

__host__ __device__ constexpr int xfield(int r, int e, int c) {
  return r == 9 ? 24 + e : 8 * (r / 3) + 2 * (((r % 3) + c) & 3) + (((r % 3) == 2 && c >= 2) ? 1 - e : e);
}
__host__ __device__ constexpr int blk_a(int b) { return b < 12 ? 3 * (b / 8) + ((b & 3) == 3) : (b < 15 ? 3 * (b - 12) : 3 * (b - 15)); }
__host__ __device__ constexpr int blk_b(int b) { return b < 12 ? 3 * (b < 4 ? 1 : 2) + ((b & 3) == 3 ? 0 : (b & 3)) : (b < 15 ? 3 * (b - 12) + 1 : 9); }
__host__ __device__ constexpr int slot_pq(int u, int e, int c) {
  return u < 36 ? (xfield(blk_a(u >> 1), e, c) | (xfield(blk_b(u >> 1), u & 1, c) << 8))
       : u < 39 ? (xfield(3 * (u - 36), e, c) * 257)
       : u < 42 ? (xfield(3 * (u - 39), e, c) | (xfield(3 * (u - 39) + 2, e, c) << 8))
       : u == 42 ? (xfield(3 * e, 0, c) | (xfield(3 * e, 1, c) << 8))
       : u == 43 ? (e == 0 ? (xfield(6, 0, c) | (xfield(6, 1, c) << 8))
                           : (c == 0 ? 24 * 257 : c == 1 ? 25 * 257 : c == 2 ? (24 | 25 << 8) : 26 * 257))
       : u < 47 ? (xfield(3 * (u - 44), e, c) | (26 << 8))
       : (c == 0 ? ((24 + e) | 26 << 8) : 27 * 257);
}
struct SlotTab { uint32_t v[48 * 8]; };
constexpr SlotTab make_slot_tab() {
  SlotTab t{};
  for (int u = 0; u < 48; u++)
    for (int k = 0; k < 8; k++) {
      const int pq = slot_pq(u, k & 1, k >> 1), p = pq & 255, q = pq >> 8;
      t.v[u * 8 + k] = (uint32_t)((p * 28 + q) * 4) | ((uint32_t)(((p != q && q < 26) ? q * 28 + p : 27 * 28 + 27) * 4) << 16);
    }
  return t;
}
__device__ __align__(16) const SlotTab g_slot_tab = make_slot_tab();

struct CinCtx {
  uint32_t full, bar0, jump, dslot, par, first, cin, o03, o14, o25, o69, o78, selA, selB;
  bool ones, lead, ring;
};
constexpr unsigned long long CW_DESC = (unsigned long long)((SMEM_BASE + OFF_CW) >> 4) | (8ull << 16) | (16ull << 32);
constexpr int OFF_INIT = U_SP * UNIT;
constexpr unsigned long long INIT_DESC = (unsigned long long)((SMEM_BASE + OFF_INIT) >> 4) | (9ull << 32);
constexpr unsigned long long ONES_DESC = (SMEM_BASE + OFF_INIT + 4608) >> 4;
constexpr unsigned long long CWL_DESC = CW_DESC + (OFF_CWL - OFF_CW) / 16;

template <int U>
__device__ __forceinline__ uint32_t zreg(const uint32_t (&x)[10][2], int h, const CinCtx& c) {
  if constexpr (U < 36) {
    if constexpr (U & 1) return mul2hi(x[blk_a(U >> 1)][h], x[blk_b(U >> 1)][h]);
    else return mul2lo(x[blk_a(U >> 1)][h], x[blk_b(U >> 1)][h]);
  } else if constexpr (U < 39) {
    return mul2(x[3 * (U - 36)][h], x[3 * (U - 36)][h]);
  } else if constexpr (U < 42) {
    return mul2(x[3 * (U - 39)][h], x[3 * (U - 39) + 2][h]);
  } else if constexpr (U == 42) {
    return mul2(__byte_perm(x[0][h], x[3][h], 0x5410), __byte_perm(x[0][h], x[3][h], 0x7632));
  } else {
    const uint32_t f = c.ones ? 0x3f803f80u : x[9][h];
    return mul2(__byte_perm(x[6][h], f, c.selA), __byte_perm(x[6][h], f, c.selB));
  }
}

__host__ __device__ constexpr int kord(int s) { return s; }
template <int S0, int NS>
struct ZGroup {
  uint32_t z[NS][4];
  template <int I = 0>
  __device__ __forceinline__ void fill(const uint32_t (&x)[10][2], const CinCtx& c) {
    if constexpr (I < NS) {
      z[I][0] = zreg<2 * kord(S0 + I)>(x, 0, c);
      z[I][1] = zreg<2 * kord(S0 + I)>(x, 1, c);
      z[I][2] = zreg<2 * kord(S0 + I) + 1>(x, 0, c);
      z[I][3] = zreg<2 * kord(S0 + I) + 1>(x, 1, c);
      fill<I + 1>(x, c);
    }
  }
  template <int I = 0>
  __device__ __forceinline__ void mma(float (&acc)[28]) {
    if constexpr (I < NS) {
      constexpr int S = kord(S0 + I);
      wgmma_rs_n56<CW_DESC + (S < CW_CUT ? S * 1792 : OFF_CW2 - OFF_CW + (S - CW_CUT) * 1792) / 16, (S0 + I) != 0>(acc, z[I][0], z[I][1], z[I][2], z[I][3]);
      mma<I + 1>(acc);
    }
  }
};

__device__ __forceinline__ void cin_finish(const CinCtx& c, float (&acc)[28], uint32_t out) {
#pragma unroll
  for (int i = 0; i < 28; i++) asm volatile("" : "+f"(acc[i]));
  float s0 = acc[12] * acc[13], s1 = acc[14] * acc[15];
#pragma unroll
  for (int i = 0; i < 12; i += 2) {
    s0 = fmaf(acc[i], acc[16 + i], s0);
    s1 = fmaf(acc[i + 1], acc[17 + i], s1);
  }
  sts32f(out, s0 + s1);
}

__device__ __forceinline__ void cin_ldsm(const CinCtx& c, uint32_t so, uint32_t (&x)[10][2]) {
  ldsm4t(x[0][0], x[0][1], x[3][0], x[3][1], so + c.o03);
  ldsm4t(x[1][0], x[1][1], x[4][0], x[4][1], so + c.o14);
  ldsm4t(x[2][0], x[2][1], x[5][0], x[5][1], so + c.o25);
  ldsm4t(x[6][0], x[6][1], x[9][0], x[9][1], so + c.o69);
  ldsm4t(x[7][0], x[7][1], x[8][0], x[8][1], so + c.o78);
}
__device__ __forceinline__ void cin_load(const CinCtx& c, int k, bool real, uint32_t (&x)[10][2]) {
  if (real) mbar_wait(c.full + 8 * k, c.par);
  cin_ldsm(c, k * XSLOT, x);
  if (c.lead) mbar_arrive(c.full + 8 * k + 64);
}
__device__ __forceinline__ void cin_advance(CinCtx& c, int j) {
  const bool jump = j == c.jump, wrap = jump && c.ring;
  const uint32_t d = jump ? c.dslot : 2 * XSLOT;
  c.o03 += d; c.o14 += d; c.o25 += d; c.o69 += d; c.o78 += d;
  c.full += wrap ? -48 : 16;
  c.par ^= wrap;
  c.jump += wrap ? 8 : 0;
  c.cin += 2 * CROW;
}
constexpr int CG_SIZE = 2;
constexpr int CG_WAIT = 3;
constexpr int CG_HEAD = 3;
constexpr int CG_LIN = 3;
constexpr int CG_LOAD = 4;
constexpr int CG_N = (22 + CG_SIZE - 1) / CG_SIZE;
template <int G, int GEND>
__device__ __forceinline__ void cin_groups(const CinCtx& c, const uint32_t (&x)[10][2], float (&acc)[28],
                                           int q, bool more, uint32_t (&xn)[10][2]) {
  if constexpr (G < GEND) {
    constexpr int S0 = G * CG_SIZE, NS = (S0 + CG_SIZE <= 22) ? CG_SIZE : 22 - S0;
    ZGroup<S0, NS> g; g.fill(x, c);
    if constexpr (G == CG_LIN) {
      wg_fence();
      wgmma_rs_n32<CWL_DESC, 1>(acc, x[0][0], x[0][1], x[3][0], x[3][1]);
      wgmma_rs_n32<CWL_DESC + 1024 / 16, 1>(acc, x[6][0], x[6][1], x[9][0], x[9][1]);
      wg_commit();
    }
    wg_fence();
    g.mma(acc);
    wg_commit();
    if constexpr (G == CG_LOAD) cin_load(c, q, more, xn);
    if constexpr (G != CG_HEAD - 1) {
      if constexpr (G >= CG_LIN && G < CG_LIN + CG_WAIT) wg_wait<CG_WAIT + 1>(); else wg_wait<CG_WAIT>();
    }
    cin_groups<G + 1, GEND>(c, x, acc, q, more, xn);
  }
}
__device__ __forceinline__ void cin_head(const CinCtx& c, uint32_t (&x)[10][2], float (&acc)[28]) {
  cin_groups<0, CG_HEAD>(c, x, acc, 0, false, x);
}
__device__ __forceinline__ void cin_tail(const CinCtx& c, const uint32_t (&x)[10][2], float (&acc)[28],
                                         int q, bool more, uint32_t (&xn)[10][2]) {
  cin_groups<CG_HEAD, CG_N>(c, x, acc, q, more, xn);
}

__device__ __forceinline__ void cin_setup(CinCtx& c, uint32_t sb, int wg, int warp, int lane, bool gemm) {
  c.full = sb + OFF_BAR + 8 * (BAR_CFULL + wg * 16); c.bar0 = sb + OFF_BAR + 8 * (BAR_C0 + wg);
  c.par = 0; c.lead = lane == 0 && !gemm; c.ring = !gemm;
  const uint32_t ring = !gemm ? XOFF_SLOT + 8 * wg * XSLOT : wg ? 10 * UNIT : OFF_GIDX + XSLOT;
  c.first = (!gemm ? OFF_GIDX + wg * XSLOT : wg ? 24 * UNIT : OFF_GIDX) - ring;
  c.jump = gemm && !wg ? 0 : 6;
  c.dslot = !gemm ? -6 * XSLOT : wg ? 11 * UNIT - 6 * XSLOT : 14 * UNIT - OFF_GIDX - XSLOT;
  const int m = lane >> 4, f0 = lane & 7, f1 = (f0 + 2) & 7, f2 = (f0 ^ 4) ^ (f0 >> 2);
  const uint32_t base = sb + ring, ch = (warp & 3) * 2 + ((lane >> 3) & 1);
  const int f3 = m ? f0 & 1 : f0, f4 = m ? f2 : f1;
  c.o03 = base + (8 * m + f0) * 128 + ((ch ^ f0) << 4);
  c.o14 = base + (8 * m + f1) * 128 + ((ch ^ f1) << 4);
  c.o25 = base + (8 * m + f2) * 128 + ((ch ^ f2) << 4);
  c.o69 = base + (16 + 8 * m + f3) * 128 + ((ch ^ f3) << 4);
  c.o78 = base + (16 + f4) * 128 + ((ch ^ f4) << 4);
  const int q = lane & 3;
  c.selA = q == 1 ? 0x7610 : 0x5410;
  c.selB = q == 0 ? 0x5432 : 0x7632;
  c.ones = q == 3;
}
template <typename F0, typename F, typename F2>
__device__ __forceinline__ void cin_run(CinCtx& c, int nj, F0 after_load, F after_start, F2 before_end) {
  float accA[28], accB[28];
  uint32_t xA[10][2], xB[10][2];
  mbar_wait(c.bar0, 0);
  cin_ldsm(c, c.first, xA);
  after_load();
  cin_head(c, xA, accA);
  after_start();
#pragma unroll 1
  for (int j = 0;; j += 2) {
    const uint32_t out = c.cin;
    cin_tail(c, xA, accA, 0, j + 1 < nj, xB);
    if (j + 1 >= nj) { before_end(); wg_wait<0>(); cin_finish(c, accA, out); break; }
    cin_head(c, xB, accB);
    wg_wait<CG_HEAD>();
    cin_finish(c, accA, out);
    cin_tail(c, xB, accB, 1, j + 2 < nj, xA);
    if (j + 2 >= nj) { before_end(); wg_wait<0>(); cin_finish(c, accB, out + CROW); break; }
    cin_head(c, xA, accA);
    wg_wait<CG_HEAD>();
    cin_finish(c, accB, out + CROW);
    cin_advance(c, j);
  }
}

constexpr float ALPHA = 0.3292034911525734f, KAPPA = 2.423681954311584f;
__device__ __forceinline__ float gelu_acc(float v, float ab, float w, float s) {
  const float a = fmaf(v, ALPHA, ab);
  const float u = a * fmaf(a, a, KAPPA);
  float th; asm("tanh.approx.f32 %0, %1;" : "=f"(th) : "f"(u));
  return fmaf(fmaf(a, th, a), w, s);
}

constexpr int QD = 1;
template <int NG>
struct Gelu {
  float4 q[QD + 1];
  float ab;
  uint32_t ep;
  __device__ __forceinline__ void start(uint32_t a) {
    ep = a;
#pragma unroll
    for (int i = 0; i < QD; i++) q[i] = lds128f(ep + i * 64);
  }
  __device__ __forceinline__ void gate(uint32_t sb, uint32_t zero) {
    asm volatile("{\n.reg .pred p;\nsetp.ne.u32 p, %2, 0;\n@p st.shared.b32 [%1], %2;\nld.shared.f32 %0, [%1];\n}" : "=f"(ab) : "r"(sb + OFF_EPI + 1024), "r"(zero) : "memory");
  }
  template <int I0, int I1>
  __device__ __forceinline__ void part(float (&d)[4 * NG], float& r0, float& r1) {
#pragma unroll
    for (int i = I0; i < I1; i++) {
      if (!(i & 1) && i / 2 + QD < NG / 2) q[(i / 2 + QD) % (QD + 1)] = lds128f(ep + (i / 2 + QD) * 64);
      const float4 v = q[(i / 2) % (QD + 1)];
      const float w0 = i & 1 ? v.z : v.x, w1 = i & 1 ? v.w : v.y;
#pragma unroll
      for (int e = 0; e < 4; e++) asm volatile("" : "+f"(d[4 * i + e]));
      r0 = gelu_acc(d[4 * i + 0], ab, w0, r0);
      r0 = gelu_acc(d[4 * i + 1], ab, w1, r0);
      r1 = gelu_acc(d[4 * i + 2], ab, w0, r1);
      r1 = gelu_acc(d[4 * i + 3], ab, w1, r1);
    }
    asm volatile("" : "+f"(r0), "+f"(r1));
  }
};
__device__ __forceinline__ void pin(float a, float b, uint32_t addr, uint32_t zero) {
  asm volatile("{\n.reg .pred p;\nsetp.ne.u32 p, %3, 0;\n@p st.shared.v2.f32 [%0], {%1, %2};\n}" ::"r"(addr), "f"(a), "f"(b), "r"(zero) : "memory");
}
__device__ __forceinline__ void hand_on(float (&d)[96], const float (&s)[96]) {
#pragma unroll
  for (int i = 0; i < 96; i++) asm volatile("mov.b32 %0, %1;" : "=f"(d[i]) : "f"(s[i]));
}
__device__ __forceinline__ uint64_t desc_x(int u) { return mkdesc(SMEM_BASE, 16, 1024, 1) + u * (UNIT / 16); }
__device__ __forceinline__ uint64_t desc_w(int u, int stride = 1) { return mkdesc(SMEM_BASE, stride * UNIT, 1024, 1) + u * (UNIT / 16); }
__device__ __forceinline__ void tile_step(float (&d)[96], uint64_t dA, uint64_t dB) {
  wg_fence();
#pragma unroll
  for (int k = 0; k < 4; k++) wgmma_ss_n192(d, dA + 2 * k, dB + 128 * k, 1);
  wg_commit();
}
template <int K0 = 0, int K1 = 4>
__device__ __forceinline__ void wide_step(float (&d)[96], float (&e)[32], uint64_t dA, uint64_t dB) {
  wg_fence();
#pragma unroll
  for (int k = K0; k < K1; k++) wgmma_ss_n256(d, e, dA + 2 * k, dB + 128 * k, 1);
  wg_commit();
}
__device__ __forceinline__ int slot_of(int wg, int j) {
  return wg ? (j == 0 ? 24 * UNIT : j <= 8 ? 10 * UNIT + (j - 1) * XSLOT : 21 * UNIT + (j - 9) * XSLOT)
            : (j < 3 ? OFF_GIDX + j * XSLOT : 14 * UNIT + (j - 3) * XSLOT);
}

__device__ __forceinline__ int cin_start(int c) {
  return c < NGEMM ? c * NC_GEMM + min(c, NBIG) : NB - (GRID - c) * NC_EXTRA;
}
__device__ __forceinline__ int cin_count(int c) {
  return c < NGEMM ? NC_GEMM + (c < NBIG) : NC_EXTRA;
}

__device__ __forceinline__ int fold_i0(int e) { return e < 2 ? 7 * e : 2 + 6 * e; }
__device__ __forceinline__ uint32_t ldg16(const void* p) { uint16_t v; asm volatile("ld.global.nc.u16 %0, [%1];" : "=h"(v) : "l"(p)); return v; }
__device__ __forceinline__ uint4 ldg128(const void* p) {
  uint4 v; asm volatile("ld.global.nc.v4.u32 {%0,%1,%2,%3}, [%4];" : "=r"(v.x), "=r"(v.y), "=r"(v.z), "=r"(v.w) : "l"(p)); return v;
}
__device__ __forceinline__ void sts64f(uint32_t addr, float a, float b) { asm volatile("st.shared.v2.f32 [%0], {%1, %2};" ::"r"(addr), "f"(a), "f"(b) : "memory"); }
__device__ __forceinline__ float to_tf32(float v) { uint32_t r; asm("cvt.rna.tf32.f32 %0, %1;" : "=r"(r) : "f"(v)); return __uint_as_float(r); }
__device__ __forceinline__ uint4 fold_chunk(uint32_t base, const uint4 t0, const uint4 t1) {
  const uint32_t t[8] = {t0.x, t0.y, t0.z, t0.w, t1.x, t1.y, t1.z, t1.w};
  uint32_t v[4];
#pragma unroll
  for (int c = 0; c < 4; c++) {
    const float w0 = __int_as_float(lds32(base + (t[2 * c] & 0xffff))) + __int_as_float(lds32(base + (t[2 * c] >> 16)));
    const float w1 = __int_as_float(lds32(base + (t[2 * c + 1] & 0xffff))) + __int_as_float(lds32(base + (t[2 * c + 1] >> 16)));
    __nv_bfloat162 pk = __floats2bfloat162_rn(w0, w1);
    v[c] = *reinterpret_cast<uint32_t*>(&pk);
  }
  return make_uint4(v[0], v[1], v[2], v[3]);
}
__device__ __forceinline__ int cw_chunk(int u, int n) {
  return ((u < 44 ? (u >> 1) * 1792 : CW_MAIN + ((u - 44) >> 1) * 1024) + (n >> 3) * 256 + (u & 1) * 128 + (n & 7) * 16) >> 4;
}
__device__ __forceinline__ void fold_weights(uint8_t* smem, uint32_t sb, int e, const __nv_bfloat16* __restrict__ wco, const GPtr gp) {
  const int tid = threadIdx.x, lane = tid & 31, warp = tid >> 5;
  const uint32_t bars = sb + OFF_BAR;
  const int i0 = fold_i0(e), i = i0 + warp;
  const bool own = i < fold_i0(e + 1);
  const uint32_t wb16 = ldg16(wco + (lane < NF ? 26 + lane : 0)), wc16 = ldg16(wco + (lane < NF ? 52 + lane : 0));
  const uint32_t w116 = ldg16(wco + (own ? i : 0));
  const uint4* tab = gp.tab;
  const uint4 ta0 = ldg128(tab + 2 * lane), ta1 = ldg128(tab + 2 * lane + 1);
  const uint4 tb0 = ldg128(tab + 64 + 2 * (lane & 15)), tb1 = ldg128(tab + 65 + 2 * (lane & 15));
  asm volatile("barrier.cluster.arrive.relaxed.aligned;\nbarrier.cluster.wait.acquire.aligned;" ::: "memory");
  if (warp >= 6) {
    for (int t = tid - 192; t < 6 * 20; t += 64) sts64f(sb + XOFF_M + 26 * 160 + t * 8, 0.f, 0.f);
    if (warp == 6 && lane < NF) {
      sts64f(sb + XOFF_M + lane * 160 + 104, bf_lo(wb16), 0.f);
      sts64f(sb + XOFF_M + lane * 160 + 112, 0.f, 0.f);
      sts64f(sb + XOFF_M + lane * 160 + 120, 0.f, 0.f);
    }
    if (warp == 7) {
      gp.s->cw[cw_chunk(lane, 28 + e)] = make_uint4(0, 0, 0, 0);
      if (lane < 16) gp.s->cw[cw_chunk(32 + lane, 28 + e)] = make_uint4(0, 0, 0, 0);
    }
  } else {
    mbar_wait(bars + 8 * BAR_GIDX, 0);
    float m0 = 0.f, m1 = 0.f, m2 = 0.f, m3 = 0.f;
    const uint32_t a = sb + XOFF_W3 + (tid < 169 ? tid : 0) * 8;
#pragma unroll 2
    for (int g = 0; g < NF; g++) {
      const int2 v = lds64(a + g * 1352);
      const float w = __shfl_sync(0xffffffffu, bf_lo(wc16), g);
      m0 = fmaf(w, bf_lo(v.x), m0); m1 = fmaf(w, bf_hi(v.x), m1);
      m2 = fmaf(w, bf_lo(v.y), m2); m3 = fmaf(w, bf_hi(v.y), m3);
    }
    if (tid < 169) {
      const int o = tid * 2, o2 = o + 1;
      sts64f(sb + XOFF_M + (o / 13) * 160 + (o % 13) * 8, to_tf32(m0), to_tf32(m1));
      sts64f(sb + XOFF_M + (o2 / 13) * 160 + (o2 % 13) * 8, to_tf32(m2), to_tf32(m3));
    }
  }
  const uint32_t sT = sb + XOFF_S + warp * 2 * 3136, sA = sT + 3136;
  const int g = lane >> 2, c = lane & 3;
  uint32_t af[2][8];
  mbar_wait(bars + 8 * BAR_FULL, 0);
  if (own) {
#pragma unroll
    for (int k = 0; k < 8; k++) {
      const int h = 4 * k + c;
      const uint32_t a = sb + XOFF_W2 + ((h < NF ? h : 0) * 676 + i * 26 + 2 * g) * 2;
      af[0][k] = lds32(a);
      af[1][k] = lds32(a + (g < 5 ? 32 : 0));
    }
#pragma unroll 1
    for (int o = lane; o < 338; o += 32) {
      const uint32_t v = lds32(sb + XOFF_W1 + (i - (i0 & ~1)) * 1352 + o * 4);
      sts64f(sA + (o / 13) * 112 + (o % 13) * 8, bf_lo(v), bf_hi(v));
    }
    if (lane < 28) sts64f(sA + lane * 112 + 104, 0.f, 0.f);
    if (lane < 2) sts64f(sT + (26 + lane) * 112 + 104, lane == 0 ? bf_lo(w116) : 0.f, 0.f);
  }
  bar_sync<4, 256>();
  if (own) {
#pragma unroll 1
    for (int n = 0; n < 4; n++) {
      float d[2][4] = {};
#pragma unroll
      for (int ks = 0; ks < 4; ks++) {
        const uint32_t b0 = lds32(sb + XOFF_M + (8 * ks + c) * 160 + (8 * n + g) * 4);
        const uint32_t b1 = lds32(sb + XOFF_M + (8 * ks + c + 4) * 160 + (8 * n + g) * 4);
#pragma unroll
        for (int m = 0; m < 2; m++)
          asm volatile("mma.sync.aligned.m16n8k8.row.col.f32.tf32.tf32.f32 {%0,%1,%2,%3}, {%4,%5,%6,%7}, {%8,%9}, {%0,%1,%2,%3};"
                       : "+f"(d[m][0]), "+f"(d[m][1]), "+f"(d[m][2]), "+f"(d[m][3])
                       : "r"(af[m][2 * ks] << 16), "r"(af[m][2 * ks] & 0xffff0000u), "r"(af[m][2 * ks + 1] << 16),
                         "r"(af[m][2 * ks + 1] & 0xffff0000u), "r"(b0), "r"(b1));
      }
      if (n < 3 || c < 2) {
        const uint32_t a = sT + 2 * g * 112 + (8 * n + 2 * c) * 4;
        sts64f(a, d[0][0], d[0][1]);
        sts64f(a + 112, d[0][2], d[0][3]);
        if (g < 5) {
          sts64f(a + 16 * 112, d[1][0], d[1][1]);
          sts64f(a + 17 * 112, d[1][2], d[1][3]);
        }
      }
    }
    __syncwarp();
    const int nt = i < 24 ? i : 2 * i - 24, na = i < 24 ? 32 + i : 2 * i - 23;
#pragma unroll 1
    for (int k = 0; k < 3; k++) {
      const bool isa = k == 1 || (k == 2 && lane >= 16);
      const uint4 v = fold_chunk(isa ? sA : sT, k < 2 ? ta0 : tb0, k < 2 ? ta1 : tb1);
      if (k < 2 || lane < 28 || na < 32) gp.s->cw[cw_chunk(k < 2 ? lane : 32 + (lane & 15), isa ? na : nt)] = v;
    }
  }
  __syncwarp();
  if (lane == 0) flag_add(&gp.s->foldflag);
  bar_sync<4, 256>();
  mbar_wait(bars + 8 * BAR_GDONE, 0);
  if (tid >= 128 && tid < 132) mbar_arrive(ev_bar(bars, EV_END));
}

__global__ void __cluster_dims__(2, 1, 1) __launch_bounds__(384, 1)
xdeepfm_kernel(const int* __restrict__ idx, const __nv_bfloat16* __restrict__ table, const __nv_bfloat16* __restrict__ w1,
               const __nv_bfloat16* __restrict__ b1, const __nv_bfloat16* __restrict__ w2,
               const __nv_bfloat16* __restrict__ ws, const __nv_bfloat16* __restrict__ wco,
               const __nv_bfloat16* __restrict__ bout, __nv_bfloat16* __restrict__ out, const GPtr gp,
               const __grid_constant__ CUtensorMap tmW, const __grid_constant__ CUtensorMap tmT) {
  int myidx, idx1, idx2 = 0, idx3 = 0;
  {
    const int t = threadIdx.x, b = blockIdx.x, half = (b >> 1) ^ (t >= 256 ? t >> 4 : 0);
    const int* ip = idx + (((b >> 3) & 15) * 256 + (half & 1) * 128 + (t < 256 ? min(min(t >> 5, 4) * 4 + (t >> 5) * 16 + min(t & 31, 19), 127) : (b & 1) * 64 + ((t >> 1) & 48) + (t & 15))) * NF;
    asm volatile("{\n.reg .pred p;\nsetp.ge.u32 p, %5, 256;\nld.global.nc.v2.s32 {%0, %1}, [%4];\n@p ld.global.nc.v2.s32 {%2, %3}, [%4 + 8];\n}"
                 : "=r"(myidx), "=r"(idx1), "+r"(idx2), "+r"(idx3) : "l"(ip), "r"(t));
  }
  extern __shared__ __align__(1024) uint8_t smem[];
  const uint32_t sb = (uint32_t)__cvta_generic_to_shared(smem);
  const uint32_t bars = sb + OFF_BAR;
  const int tid = threadIdx.x, lane = tid & 31;
  const int warp = __shfl_sync(0xffffffffu, tid >> 5, 0);
  const int cta = blockIdx.x;
  const bool gemm = cta < NGEMM;
  const int nt = cta & 7, rank = cta & 1;

  uint32_t sx, sw;
  uint4 bv;
  asm volatile("{\n.reg .pred p;\nsetp.eq.u32 p, %9, 7;\n@p ld.global.nc.u32 %0, [%6];\n@p ld.global.nc.u32 %1, [%7];\n@p ld.global.nc.v4.u32 {%2, %3, %4, %5}, [%8];\n}"
               : "=r"(sx), "=r"(sw), "=r"(bv.x), "=r"(bv.y), "=r"(bv.z), "=r"(bv.w)
               : "l"(table + cta * 256 + lane * 8), "l"(w1 + nt * 192 + lane * 2),
                 "l"(b1 + (lane < 24 ? nt * 192 : 1536 - 192 + (nt >> 2) * 64) + lane * 8), "r"(tid >> 5));
  if (warp == 8 && elect1()) {
    mbar_init(bars + 8 * BAR_GIDX, 1);
    mbar_init(bars + 8 * BAR_FULL, 1);
    mbar_init(bars + 8 * BAR_W0, 1);
    asm volatile("fence.mbarrier_init.release.cluster;" ::: "memory");
    if (gemm) {
      mbar_expect_tx(bars + 8 * BAR_W0, 4 * UNIT);
#pragma unroll
      for (int i = 0; i < 4; i++)
        tma_load(sb + (U_W + i) * UNIT, &tmW, i < 3 ? nt * 192 + i * 64 : 1536 + (nt >> 2) * 64, 0, bars + 8 * BAR_W0);
    } else {
      mbar_expect_tx(bars + 8 * BAR_GIDX, 35152);
      bulk_load(sb + XOFF_W3, ws + 2 * 17576, 35152, bars + 8 * BAR_GIDX);
    }
  }
  if (threadIdx.x < 256) {}
  else if (threadIdx.x >= 384 - 16) {
    const int l = threadIdx.x & 7;
    if (l < 7) asm volatile("prefetch.global.L2 [%0];" ::"l"(w1 + (((cta >> 3 & 15) * 2 + (cta & 1)) * 2 + ((threadIdx.x >> 3) & 1)) * DIN + (l < 6 ? (cta & 6) * 192 + l * 64 : 1536 + (cta & 4) * 16)));
  }
  else if (threadIdx.x >= 352 && threadIdx.x < 359) {
    const int l = blockIdx.x * 7 + threadIdx.x - 352;
    if (l < 824) asm volatile("prefetch.global.L2 [%0];" ::"l"(ws + (823 - l) * 64));
  }

  const int c0 = cin_start(cta), ncin = cin_count(cta);

  if (warp >= 8) {
    const int pw = warp - 8;
    const uint32_t cidx = sb + (gemm ? OFF_CIDX : XOFF_CIDX);
    const bool lead = elect1();
    if (lead) {
      if (pw) mbar_init(bars + 8 * (pw < 3 ? BAR_FULL + pw : BAR_CIDX), 1);
      else mbar_init(bars + 8 * BAR_GDONE, 4);
      asm volatile("fence.mbarrier_init.release.cluster;" ::: "memory");
    }
    __syncwarp();
    asm volatile("barrier.cluster.arrive.relaxed.aligned;" ::: "memory");
    if (lead) {
      if (gemm) w_prefetch(w1, 1, cta, pw);
      if (pw == 0) {
        if (gemm) {
          mbar_expect_tx(bars + 8 * BAR_FULL, 2 * UNIT);
          asm volatile("prefetch.tensormap [%0];" ::"l"(&tmT) : "memory");
        } else {
          const int i0 = fold_i0(cta - NGEMM) & ~1, ni = NF - i0 < 8 ? NF - i0 : 8;
          mbar_expect_tx(bars + 8 * BAR_FULL, 35152 + ni * 1352);
          bulk_load(sb + XOFF_W1, ws + i0 * 676, ni * 1352, bars + 8 * BAR_FULL);
          bulk_load(sb + XOFF_W2, ws + 17576, 35152, bars + 8 * BAR_FULL);
        }
      } else if (pw == 3 && !gemm) {
        const int a0 = c0 & ~1, a1 = (c0 + ncin + 1) & ~1;
        mbar_expect_tx(bars + 8 * BAR_CIDX, (a1 - a0) * NF * 4);
        bulk_load(cidx, idx + a0 * NF, (a1 - a0) * NF * 4, bars + 8 * BAR_CIDX);
      }
    }
    __syncwarp();
    asm volatile("setmaxnreg.dec.sync.aligned.u32 24;");
    if (elect1()) {
      mbar_init(bars + 8 * (BAR_EV + pw), 4);
      mbar_init(bars + 8 * (BAR_EV + 4 + pw), 4);
      mbar_init(bars + 8 * (BAR_FULL + 4 + pw), 1);
      mbar_init(bars + 8 * (pw == 2 ? BAR_CW : BAR_DNN + pw), pw == 2 ? 1 : 1 << pw);
      if (pw == 0) mbar_init(bars + 8 * (BAR_FULL + 3), 1);
#pragma unroll
      for (int i = 0; i < 8; i++)
        mbar_init(bars + 8 * (BAR_CFULL + pw * 8 + i), (!gemm && (pw & 1)) ? 4 : 1);
      if (pw < 2) mbar_init(bars + 8 * (BAR_C0 + pw), 1);
      asm volatile("fence.mbarrier_init.release.cluster;" ::: "memory");
    }
    __syncwarp();
    bar_sync<6, 128>();
    asm volatile("barrier.cluster.wait.acquire.aligned;" ::: "memory");
    if (!gemm && elect1()) mbar_arrive(bars + 8 * BAR_GDONE);
    __syncwarp();
    if (gemm) {
      {
        const uint32_t a = sb + OFF_GIDX + ((lane >> 4) * 64 + pw * 16 + (lane & 15)) * NF * 4;
        asm volatile("st.shared.v2.b32 [%0], {%1, %2};\nst.shared.v2.b32 [%0 + 8], {%3, %4};"
                     ::"r"(a), "r"(myidx), "r"(idx1), "r"(idx2), "r"(idx3) : "memory");
        __syncwarp();
      }
      if (elect1()) {
#pragma unroll
        for (int j = 0; j < 16; j += 8) {
          int r[8];
#pragma unroll
          for (int i = 0; i < 8; i++) r[i] = lds32(sb + OFF_GIDX + ((64 + pw * 16 + j + i) * NF) * 4);
#pragma unroll
          for (int i = 0; i < 8; i++) tma_row_mc(sb + U_XB * UNIT + (rank * 64 + pw * 16 + j + i) * 128, &tmT, r[i], bars + 8 * BAR_FULL);
        }
        int s = 1;
#pragma unroll 1
        for (int fi = 1; fi < NF; fi++) {
          const int f = fresh(fi), pw = fresh(warp) - 8, ct = fresh(cta), nt = ct & 7;
          const int t = f - FS, st = t < 0 ? s : (t & 3) ^ ((t >> 1) & 1), e = f - 3 - (t > 1);
          const uint32_t fb = bars + 8 * (BAR_FULL + (f & 7)), ia = sb + OFF_GIDX + (pw * 16 * NF + f) * 4;
          const uint32_t d = sb + (st == 3 ? U_SP : 2 * st) * UNIT + ((ct & 1) * 64 + pw * 16) * 128;
          if (f == 4) mbar_wait(bars + 8 * BAR_GIDX, 0);
          int r[2][RB];
#pragma unroll
          for (int i = 0; i < RB; i++) r[0][i] = lds32(ia + i * NF * 4);
          if (e >= 0) mbar_wait(ev_bar(bars, e), ev_par(e));
          if (pw == 0) mbar_expect_tx(fb, t < 0 ? 8 * UNIT : 6 * UNIT);
#pragma unroll
          for (int j = 0; j < 16 / RB; j++) {
#pragma unroll
            for (int i = 0; i < RB; i++) r[(j + 1) & 1][i] = lds32(ia + (RB * j + RB + i + (RB * j + RB >= 16) * 48) * NF * 4);
#pragma unroll
            for (int i = 0; i < RB; i++) tma_row_mc(d + (RB * j + i) * 128, &tmT, r[j & 1][i], fb);
          }
          if (t < 0) {
#pragma unroll
            for (int j = 0; j < 16 / RB; j++) {
              if (j + 1 < 16 / RB) {
#pragma unroll
                for (int i = 0; i < RB; i++) r[(j + 1) & 1][i] = lds32(ia + (64 + RB * j + RB + i) * NF * 4);
              }
#pragma unroll
              for (int i = 0; i < RB; i++) tma_row_mc(d + U_XB * UNIT + (RB * j + i) * 128, &tmT, r[j & 1][i], fb);
            }
          }
          tma_load(sb + (U_W + 4 * st + pw) * UNIT, &tmW, pw < 3 ? nt * 192 + pw * 64 : 1536 + (nt >> 2) * 64, f * 64, fb);
          if (f == GI && pw < 2) {
            if (pw == 0) mbar_expect_tx(bars + 8 * BAR_GIDX, 128 * NF * 4);
            bulk_load(sb + OFF_GIDX + pw * 64 * NF * 4, idx + ((ct >> 3) * 256 + (((ct >> 1) ^ pw) & 1) * 128 + (ct & 1) * 64) * NF, 64 * NF * 4, bars + 8 * BAR_GIDX);
          }
          if (f == GI && pw == 2) {
            const int c0 = cin_start(ct), a0 = c0 & ~1, n = (((c0 + cin_count(ct) + 1) & ~1) - a0) * NF * 4;
            mbar_expect_tx(bars + 8 * BAR_CIDX, n);
            bulk_load(sb + OFF_CIDX, idx + a0 * NF, n, bars + 8 * BAR_CIDX);
          }
          if (f + WD < NF) w_prefetch(w1, f + WD, ct, pw);
          if (++s == 3) s = 0;
        }
        mbar_wait(bars + 8 * BAR_T, 0);
#pragma unroll 1
        for (int ti = 0; ti < 8; ti++) {
          const int t = fresh(ti), pw = fresh(warp) - 8, e = t < 4 ? 22 - !t : 19 + t;
          const uint32_t ia = sb + OFF_TIDX + t * 256 + pw * 64, fb = bars + 8 * (BAR_FULL + ((NF + t) & 7));
          const uint32_t d = sb + b_x(t) * UNIT + ((fresh(cta) & 1) * 64 + pw * 16) * 128;
          int4 r[2];
          r[0] = lds128(ia);
          r[1] = lds128(ia + 16);
          mbar_wait(ev_bar(bars, e), ev_par(e));
          if (pw == 0) mbar_expect_tx(fb, t < 3 ? 2 * UNIT : 5 * UNIT);
#pragma unroll
          for (int j = 0; j < 4; j++) {
            tma_row_mc(d + (4 * j + 0) * 128, &tmT, r[j & 1].x, fb);
            tma_row_mc(d + (4 * j + 1) * 128, &tmT, r[j & 1].y, fb);
            tma_row_mc(d + (4 * j + 2) * 128, &tmT, r[j & 1].z, fb);
            tma_row_mc(d + (4 * j + 3) * 128, &tmT, r[j & 1].w, fb);
            if (j < 2) r[j & 1] = lds128(ia + 32 + 16 * j);
          }
        }
        mbar_arrive(bars + 8 * BAR_GDONE);
      }
      __syncwarp();
    }
    {
    int cta; asm volatile("mov.u32 %0, %%ctaid.x;" : "=r"(cta));
    cta = __shfl_sync(0xffffffffu, cta, 0);
    const bool gemm = cta < NGEMM;
    const int bt = cta >> 3, nt = cta & 7;
    const int c0 = cin_start(cta), ncin = cin_count(cta);
    const int n0 = gemm ? NC_WG0 : NC_EXTRA / 2;
    if (pw == 3) {
      if (elect1()) {
        if (!gemm) flag_wait(&gp.s->foldflag, (gp.s->epoch[fresh(cta)] + 1) * NEXTRA * 8, 0);
        asm volatile("fence.proxy.async.global;" ::: "memory");
        if (gemm) mbar_wait(ev_bar(bars, EV_CW), ev_par(EV_CW));
        mbar_expect_tx(bars + 8 * BAR_CW, CW_BYTES);
        bulk_load(sb + OFF_CW, gp.s->cw, CW_CUT * 1792, bars + 8 * BAR_CW);
        bulk_load(sb + OFF_CW2, gp.s->cw + CW_CUT * 1792 / 16, (22 - CW_CUT) * 1792, bars + 8 * BAR_CW);
        bulk_load(sb + OFF_CWL, gp.s->cw + CW_MAIN / 16, CW_LIN, bars + 8 * BAR_CW);
      }
      __syncwarp();
    }
    if (pw < 3 || !gemm) {
      if (elect1()) {
        const uint32_t cidx = sb + (gemm ? OFF_CIDX : XOFF_CIDX) + (c0 & 1) * NF * 4;
        mbar_wait(bars + 8 * BAR_GDONE, 0);
        mbar_wait(bars + 8 * BAR_CIDX, 0);
#pragma unroll 1
        for (int n = pw; n < (gemm ? 36 : NC_EXTRA); n += gemm ? 3 : 4) {
          int wg = n & 1, j = n >> 1, bi;
          uint32_t d;
          if (gemm) {
            if (n < 7) { wg = n == 4; j = n < 4 ? n : n - 1 - 3 * wg; }
            else j = wg ? j - 2 : j + 2;
            if (j >= (wg ? ncin - n0 : n0)) continue;
            if (n >= 3 && n < 6) mbar_wait(ev_bar(bars, EV_SLOT), ev_par(EV_SLOT));
            if (n >= 7 && n < 10) mbar_wait(ev_bar(bars, EV_END), ev_par(EV_END));
            bi = j - 1;
            d = sb + slot_of(wg, j);
          } else {
            bi = (j - 1) & 7;
            if (n >= 2 && n < 6) mbar_wait(ev_bar(bars, EV_END), ev_par(EV_END));
            if (j > 8) mbar_wait(bars + 8 * (BAR_CFULL + wg * 16 + 8 + bi), (((j - 1) >> 3) & 1) ^ 1);
            d = sb + (j ? XOFF_SLOT + (wg * 8 + bi) * XSLOT : OFF_GIDX + wg * XSLOT);
          }
          const uint32_t cb = bars + 8 * (j ? BAR_CFULL + wg * 16 + bi : BAR_C0 + wg);
          mbar_expect_tx(cb, NF * 128);
          const uint32_t ia = cidx + (wg * n0 + j) * NF * 4;
#pragma unroll
          for (int k = 0; k < NF; k += 2) {
            const int2 r = lds64(ia + k * 4);
            tma_row(d + k * 128, &tmT, r.x, cb);
            tma_row(d + (k + 1) * 128, &tmT, r.y, cb);
          }
        }
      }
      __syncwarp();
    }
    if (pw == 3) {
      unsigned epoch;
      asm volatile("ld.global.u32 %0, [%1];" : "=r"(epoch) : "l"(gp.s->epoch + fresh(cta)));
      epoch++;
      const float bo = (sb & 0xFFFFFF) == SMEM_BASE ? bf2f(bout[0]) : __int_as_float(0x7fc00000);
      if (gemm) {
        mbar_wait(bars + 8 * BAR_PART, 0);
        float4* dst = reinterpret_cast<float4*>(gp.s->part + nt * NB + bt * 256);
        dst[lane] = lds128f(sb + OFF_PART + lane * 16);
        dst[lane + 32] = lds128f(sb + OFF_PART + 512 + lane * 16);
        __syncwarp();
        if (lane == 0) flag_add(gp.s->dflag + (fresh(cta) >> 3) * 8);
      }
      flag_wait(gp.s->dflag + ((lane == 0 ? c0 : c0 + ncin - 1) >> 8) * 8, epoch * 8, 200);
      __syncwarp();
#pragma unroll 1
      for (int r = lane; r < ncin; r += 32) {
        float s = bo;
#pragma unroll
        for (int n = 0; n < 8; n++) s += __ldcg(gp.s->part + n * NB + c0 + r);
        sts32f(sb + OFF_DNN + r * 4, s);
      }
      __syncwarp();
      if (lane == 0) { mbar_arrive(bars + 8 * BAR_DNN); gp.s->epoch[fresh(cta)] = epoch; }
    }
    }
  } else {
    const int wg = warp >> 2;
    const int p = tid & 127;
    if (gemm) {
      asm volatile("barrier.cluster.arrive.relaxed.aligned;" ::: "memory");
      if (warp == 7) {
        asm volatile("st.shared.b32 [%0], %1;" ::"r"(sb + OFF_INIT + 4608 + lane * 4), "r"(0x3f003f00) : "memory");
        const int lg = __reduce_add_sync(0xffffffffu, (sx & 0x7fff) + ((sx >> 16) & 0x7fff) + (sw & 0x7fff) + ((sw >> 16) & 0x7fff));
        const uint32_t co = (min(max((lg >> 6) - int((127 - 11.8) * 128), 0), 130 * 128) & 0x7f80) | 0x2b;
        const uint32_t bw[4] = {bv.x, bv.y, bv.z, bv.w};
#pragma unroll
        for (int i = 0; i < 8; i++)
          asm volatile("st.shared.v4.b32 [%0], {%1, %2, %2, %2};" ::"r"(sb + OFF_INIT + lane * 144 + i * 16), "r"(__byte_perm(bw[i >> 1], co, i & 1 ? 0x5432 : 0x5410)), "r"(0) : "memory");
        sts32f(sb + OFF_EPI + 1024, -ALPHA * bf_lo(co));
        asm volatile("fence.proxy.async.shared::cta;" ::: "memory");
        bar_arrive<5, 160>();
      } else {
        const int row = min(warp, 4) * 4 + warp * 16 + (lane >> 3);
        const uint32_t a = sb + row * 128 + (((lane ^ row) & 7) << 4);
        const __nv_bfloat16* src = table + (lane & 7) * 8;
        const int l0 = ((fresh(a) >> 7) & 3) | (fresh((int)(size_t)src) & 1);
#pragma unroll
        for (int i = 0; i < 5; i++)
          asm volatile("{\n.reg .pred p;\n.reg .b32 r;\n.reg .b64 a;\nsetp.ne.b32 p, %4, 0;\nshfl.sync.idx.b32 r, %2, %3, 31, 0xffffffff;\n"
                       "mad.wide.s32 a, r, 128, %1;\n@p cp.async.cg.shared.global [%0], [a], 16;\n}"
                       ::"r"((a ^ (i & 1) * 64) + i * 512), "l"(src), "r"(myidx), "r"(4 * i + l0), "r"(int(i < 4 || warp < 4)) : "memory");
      }
      pin(__int_as_float(myidx ^ idx1), __int_as_float(idx2 ^ idx3), sb, (uint32_t)(size_t)table & 1);
      asm volatile("barrier.cluster.wait.acquire.aligned;" ::: "memory");
    } else {
      fold_weights(smem, sb, cta - NGEMM, wco, gp);
    }
    asm volatile("setmaxnreg.inc.sync.aligned.u32 224;");
    float r0 = 0.f, r1 = 0.f, r2 = 0.f, r3 = 0.f;
    float d1[96];
    const uint32_t ep = sb + OFF_EPI + (lane & 3) * 16;
    auto load_w = [&](int t) {
      const int w = warp & 3;
      if (w < 3 && elect1())
        tma_load(sb + (b_w(t) + b_ws(t) * w) * UNIT, &tmW, nt * 192 + w * 64, (NF - 1 - t) * 64, bars + 8 * (BAR_FULL + ((NF + t) & 7)));
    };
    int role; asm volatile("mov.u32 %0, %%ctaid.x;" : "=r"(role));
    role = role < NGEMM ? wg : 2;
    if (fresh(role) == 0) {
      asm volatile("setmaxnreg.inc.sync.aligned.u32 256;");
      float d0[96], dx[32], dw[96];
      Gelu<24> g0;
      bar_sync<5, 160>();
      wg_fence();
      wgmma_ss_n256<0>(dw, dx, ONES_DESC, INIT_DESC, 0);
      wgmma_ss_n192<0>(d0, ONES_DESC, INIT_DESC, 0);
      wg_commit();
      mbar_wait(bars + 8 * BAR_W0, 0);
      asm volatile("cp.async.wait_all;" ::: "memory");
      asm volatile("fence.proxy.async.shared::cta;" ::: "memory");
      bar_sync<2, 256>();
      const uint64_t dA0 = desc_x(rank), dA1 = desc_x(rank ^ 1);
      wg_fence();
#pragma unroll
      for (int k = 0; k < 4; k++) {
        wgmma_ss_n256(dw, dx, dA0 + 2 * k, desc_w(U_W) + 128 * k, 1);
        wgmma_ss_n192(d0, dA1 + 2 * k, desc_w(U_W) + 128 * k, 1);
      }
      wg_commit();
      constexpr unsigned long long STAGES = 0xb4b4924924924ull;
#pragma unroll 1
      for (int f = 1; f < NF - 3; f++) {
        mbar_wait(bars + 8 * (BAR_FULL + (f & 7)), (f >> 3) & 1);
        const int st = (STAGES >> (2 * f)) & 3, xo = (st == 3 ? U_SP : 2 * st) * (UNIT / 16);
        const uint64_t dB = desc_w(U_W + 4 * st);
        wg_fence();
        wgmma_ss_n256(dw, dx, dA0 + xo, dB, 1);
        wgmma_ss_n192(d0, dA1 + xo, dB, 1);
        wg_commit();
        wg_wait<1>();
        if (p < (f > FS ? 4 : 2)) mbar_arrive_cta(ev_bar(bars, f - 1), p & 1);
#pragma unroll
        for (int k = 1; k < 4; k++) {
          wgmma_ss_n256(dw, dx, dA0 + xo + 2 * k, dB + 128 * k, 1);
          wgmma_ss_n192(d0, dA1 + xo + 2 * k, dB + 128 * k, 1);
        }
        wg_commit();
      }
      {
        constexpr int x3 = 2 * (UNIT / 16), x4 = U_SP * (UNIT / 16), x5 = 4 * (UNIT / 16);
        const uint64_t dB3 = desc_w(U_W + 4), dB4 = desc_w(U_W + 12), dB5 = desc_w(U_W + 8);
        mbar_wait(bars + 8 * (BAR_FULL + 7), 0);
        tile_step(d0, dA1 + x3, dB3);
        wg_wait<1>();
        if (p < 4) mbar_arrive_cta(ev_bar(bars, NF - 4), p & 1);
        mbar_wait(bars + 8 * (BAR_FULL + 0), 1);
        tile_step(d0, dA1 + x4, dB4);
        mbar_wait(bars + 8 * (BAR_FULL + 1), 1);
        tile_step(d0, dA1 + x5, dB5);
        wide_step(dw, dx, dA0 + x3, dB3);
        g0.start(ep);
        wg_wait<1>();
        wide_step(dw, dx, dA0 + x4, dB4);
        g0.gate(sb, gp.zero);
        g0.part<0, PE1>(d0, r0, r1);
        pin(r0, r1, ep, gp.zero);
        wg_wait<1>();
        if (p < 4) mbar_arrive_cta(ev_bar(bars, NF - 3), p & 1);
        wide_step<0, HK>(dw, dx, dA0 + x5, dB5);
        g0.gate(sb, gp.zero);
        g0.part<PE1, PE2>(d0, r0, r1);
        pin(r0, r1, ep, gp.zero);
        wg_wait<1>();
        bar_arrive<4, 256>();
        if (p < 4) mbar_arrive_cta(ev_bar(bars, NF - 2), p & 1);
        wide_step<HK, 4>(dw, dx, dA0 + x5, dB5);
        g0.gate(sb, gp.zero);
        g0.part<PE2, PE0>(d0, r0, r1);
        pin(r0, r1, ep, gp.zero);
        wg_wait<0>();
        load_w(3);
        if (p < 4) mbar_arrive_cta(ev_bar(bars, NF - 1), p & 1);
      }
      g0.gate(sb, gp.zero);
      g0.part<PE0, 24>(d0, r0, r1);
      Gelu<8> gx;
      gx.start(ep + 12 * 64);
      gx.ab = g0.ab;
      gx.part<0, 8>(dx, r2, r3);
      hand_on(d1, dw);
      asm volatile("setmaxnreg.dec.sync.aligned.u32 224;");
    }
    if (fresh(role) == 1) {
      float d0[96], dw[96];
      bar_sync<3, 128>();
      wg_fence();
      wgmma_ss_n192<0>(d0, ONES_DESC, INIT_DESC, 0);
      wgmma_ss_n192<0>(dw, ONES_DESC + ((size_t)table & 1), INIT_DESC, 0);
      wg_commit();
      asm volatile("cp.async.wait_all;" ::: "memory");
      asm volatile("fence.proxy.async.shared::cta;" ::: "memory");
      bar_arrive<2, 256>();
      {
        const int col = p < 96 ? nt * 96 + p : 768 + (nt >> 2) * 32 + (p - 96);
        const uint32_t ww = __ldg(reinterpret_cast<const uint32_t*>(w2) + col);
        sts64f(sb + OFF_EPI + (p >> 3) * 64 + (p & 3) * 16 + (p & 4) * 2, (0.5f / ALPHA) * bf_lo(ww), (0.5f / ALPHA) * bf_hi(ww));
      }
      mbar_wait(bars + 8 * BAR_W0, 0);
      mbar_wait(bars + 8 * BAR_FULL, 0);
      wg_fence();
#pragma unroll
      for (int k = 0; k < 4; k++) {
        wgmma_ss_n192(d0, desc_x(U_XB) + 2 * k, desc_w(U_W) + 128 * k, 1);
        wgmma_ss_n192(dw, desc_x(U_XB + 1) + 2 * k, desc_w(U_W) + 128 * k, 1);
      }
      wg_commit();
      int s = 1;
#pragma unroll 1
      for (int f = 1; f < FS; f++) {
        mbar_wait(bars + 8 * (BAR_FULL + (f & 7)), (f >> 3) & 1);
        const uint64_t dA = desc_x(U_XB + 2 * s), dB = desc_w(U_W + 4 * s);
        wg_fence();
        wgmma_ss_n192(d0, dA, dB, 1);
        wgmma_ss_n192(dw, dA + 512, dB, 1);
        wg_commit();
        wg_wait<1>();
        if (p < 2) mbar_arrive_cta(ev_bar(bars, f - 1), p);
#pragma unroll
        for (int k = 1; k < 4; k++) {
          wgmma_ss_n192(d0, dA + 2 * k, dB + 128 * k, 1);
          wgmma_ss_n192(dw, dA + 512 + 2 * k, dB + 128 * k, 1);
        }
        wg_commit();
        if (++s == 3) s = 0;
      }
      wg_wait<0>();
      if (p < 2) mbar_arrive_cta(ev_bar(bars, FS - 1), p);
      {
        const uint32_t a = sb + OFF_GIDX + 64 * NF * 4;
        int v[4];
#pragma unroll
        for (int i = 0; i < 4; i++) v[i] = lds32(a + (((p & 15) * 4 + i) * NF + (NF - 1 - (p >> 4))) * 4);
        bar_sync<3, 128>();
        asm volatile("st.shared.v4.b32 [%0], {%1, %2, %3, %4};" ::"r"(sb + OFF_TIDX + p * 16), "r"(v[0]), "r"(v[1]), "r"(v[2]), "r"(v[3]) : "memory");
        bar_sync<3, 128>();
        if (p < 2) {
          flag_wait(&gp.s->foldflag, (gp.s->epoch[cta] + 1) * NEXTRA * 8, 0);
          mbar_arrive(bars + 8 * BAR_T);
        }
        __syncwarp();
      }
      mbar_wait(ev_bar(bars, FS), ev_par(FS));
      mbar_wait(bars + 8 * (BAR_FULL + 2), 1);
      bar_sync<4, 256>();
#pragma unroll
      for (int t = 0; t < 4; t++) {
        if (t) mbar_wait(bars + 8 * (BAR_FULL + 2 + t), 1);
        const uint64_t dA = desc_x(b_x(t)), dB = desc_w(b_w(t), b_ws(t));
        wg_fence();
#pragma unroll
        for (int k = 0; k < 4; k++) {
          wgmma_ss_n192(d0, dA + 2 * k, dB + 128 * k, 1);
          wgmma_ss_n192(dw, dA + 512 + 2 * k, dB + 128 * k, 1);
          if (k == 1 && t) {
            wg_commit();
            wg_wait<1>();
            mbar_wait(ev_bar(bars, NF - 1), ev_par(NF - 1));
            load_w(3 + t);
            if (t == 1 && p < 4) mbar_arrive_cta(ev_bar(bars, 26), p & 1);
            wg_fence();
          }
        }
        wg_commit();
      }
      mbar_wait(bars + 8 * (BAR_FULL + 6), 1);
      tile_step(d0, desc_x(b_x(4)), desc_w(b_w(4)));
      wg_wait<1>();
      load_w(7);
      if (p < 4) mbar_arrive(ev_bar(bars, EV_CW));
      mbar_wait(bars + 8 * (BAR_FULL + 7), 1);
      tile_step(d0, desc_x(b_x(5)), desc_w(b_w(5)));
      mbar_wait(bars + 8 * (BAR_FULL + 0), 0);
      tile_step(d0, desc_x(b_x(6)), desc_w(b_w(6)));
      mbar_wait(bars + 8 * (BAR_FULL + 1), 0);
      tile_step(d0, desc_x(b_x(7)), desc_w(b_w(7), 4));
      tile_step(dw, desc_x(b_x(4) + 1), desc_w(b_w(4)));
      Gelu<24> g0;
      g0.start(ep);
      wg_wait<1>();
      tile_step(dw, desc_x(b_x(5) + 1), desc_w(b_w(5)));
      g0.gate(sb, gp.zero);
      g0.part<0, PS>(d0, r0, r1);
      pin(r0, r1, ep, gp.zero);
      wg_wait<1>();
      if (p < 4) mbar_arrive(ev_bar(bars, 30));
      tile_step(dw, desc_x(b_x(6) + 1), desc_w(b_w(6)));
      g0.gate(sb, gp.zero);
      g0.part<PS, 2 * PS>(d0, r0, r1);
      pin(r0, r1, ep, gp.zero);
      wg_wait<1>();
      if (p < 4) mbar_arrive(ev_bar(bars, 31));
      tile_step(dw, desc_x(b_x(7) + 1), desc_w(b_w(7), 4));
      g0.gate(sb, gp.zero);
      g0.part<2 * PS, 2 * PS + PS2>(d0, r0, r1);
      pin(r0, r1, ep, gp.zero);
      wg_wait<0>();
      if (p < 4) mbar_arrive(ev_bar(bars, EV_END));
      g0.gate(sb, gp.zero);
      g0.part<2 * PS + PS2, 24>(d0, r0, r1);
      hand_on(d1, dw);
    }
    if (fresh(role) < 2) {
      Gelu<24> g1;
      g1.start(ep);
      g1.gate(sb, gp.zero);
      g1.part<0, 24>(d1, r2, r3);
    }

    {
    int cta, tid;
    asm volatile("mov.u32 %0, %%ctaid.x;" : "=r"(cta));
    asm volatile("mov.u32 %0, %%tid.x;" : "=r"(tid));
    cta = __shfl_sync(0xffffffffu, cta, 0);
    const bool gemm = cta < NGEMM;
    const int lane = tid & 31, p = tid & 127;
    const int warp = __shfl_sync(0xffffffffu, tid >> 5, 0), wg = warp >> 2;
    const int c0 = cin_start(cta), ncin = cin_count(cta);
    const int n0 = gemm ? NC_WG0 : NC_EXTRA / 2;
    CinCtx c;
    cin_setup(c, sb, wg, warp, lane, gemm);
    const int rb = wg ? n0 : 0;
    const uint32_t cinb = sb + (gemm ? OFF_CIN + rb * CROW : wg ? XOFF_CIN1 : XOFF_CIN0);
    c.cin = cinb + p * 4;
    const int nj = wg ? ncin - n0 : n0;
    uint32_t fa = cinb + (p & 7) * 16, fd = sb + OFF_DNN + rb * 4;
    __nv_bfloat16* op = out + c0 + rb;
    asm volatile("" : "+r"(fa), "+r"(fd), "+l"(op));
    auto wg_sync = [&]() { if (wg == 0) bar_sync<1, 128>(); else bar_sync<3, 128>(); };
    auto result = [&](int r, bool on) {
      const uint32_t a = fa + r * CROW;
      const float4 v0 = lds128f(a), v1 = lds128f(a + 128), v2 = lds128f(a + 256), v3 = lds128f(a + 384);
      const float dn = __int_as_float(lds32(fd + r * 4));
      float s = (((v0.x + v0.y) + (v0.z + v0.w)) + ((v1.x + v1.y) + (v1.z + v1.w))) +
                (((v2.x + v2.y) + (v2.z + v2.w)) + ((v3.x + v3.y) + (v3.z + v3.w)));
      s += __shfl_xor_sync(0xffffffffu, s, 1);
      s += __shfl_xor_sync(0xffffffffu, s, 2);
      s += __shfl_xor_sync(0xffffffffu, s, 4);
      if ((p & 7) == 0 && on) op[r] = __float2bfloat16(s + dn);
    };
    mbar_wait(bars + 8 * BAR_GDONE, 0);
    cin_run(c, nj, [&]() {
      mbar_wait(bars + 8 * BAR_CW, 0);
    }, [&]() {
      const bool b0 = lane & 1, b1_ = lane & 2;
      float a = b0 ? r1 : r0, b = b0 ? r0 : r1, cc = b0 ? r3 : r2, d = b0 ? r2 : r3;
      a += __shfl_xor_sync(0xffffffffu, b, 1);
      cc += __shfl_xor_sync(0xffffffffu, d, 1);
      float e = b1_ ? cc : a, f = b1_ ? a : cc;
      e += __shfl_xor_sync(0xffffffffu, f, 2);
      const int row = (((cta >> 1) ^ wg) & 1) * 128 + (((lane >> 1) ^ (~cta & ~wg)) & 1) * 64 + (warp & 3) * 16 + (lane & 1) * 8 + (lane >> 2);
      sts32f(sb + OFF_PART + row * 4, e);
      __syncwarp();
      if (lane == 0) mbar_arrive(bars + 8 * BAR_PART);
      mbar_wait(ev_bar(bars, gemm ? EV_CIN : EV_END), gemm);
    }, [&]() {
      mbar_wait(bars + 8 * BAR_DNN, 0);
    });
    wg_sync();
#pragma unroll 1
    for (int r = p >> 3; r < ((nj + 15) & ~15); r += 16) result(r, r < nj);
    }
  }
}

typedef CUresult (*EncodeFn)(CUtensorMap*, CUtensorMapDataType, cuuint32_t, void*, const cuuint64_t*, const cuuint64_t*,
                             const cuuint32_t*, const cuuint32_t*, CUtensorMapInterleave, CUtensorMapSwizzle,
                             CUtensorMapL2promotion, CUtensorMapFloatOOBfill);

extern "C" void kernel_launch(void* const* d_in, const int* in_sizes, int n_in, void* d_out, int out_size) {
  void* fn = nullptr;
  cudaDriverEntryPointQueryResult q;
  cudaGetDriverEntryPoint("cuTensorMapEncodeTiled", &fn, cudaEnableDefault, &q);
  EncodeFn enc = (EncodeFn)fn;
  CUtensorMap tmW, tmT;
  const cuuint32_t es[3] = {1, 1, 1};
  {
    cuuint64_t dims[2] = {DIN, DIN}, st[1] = {DIN * 2};
    cuuint32_t box[2] = {64, 64};
    enc(&tmW, CU_TENSOR_MAP_DATA_TYPE_BFLOAT16, 2, d_in[4], dims, st, box, es, CU_TENSOR_MAP_INTERLEAVE_NONE,
        CU_TENSOR_MAP_SWIZZLE_128B, CU_TENSOR_MAP_L2_PROMOTION_NONE, CU_TENSOR_MAP_FLOAT_OOB_FILL_NONE);
  }
  {
    cuuint64_t dims[2] = {64, (cuuint64_t)(in_sizes[1] / 64)}, st[1] = {128};
    cuuint32_t box[2] = {64, 1};
    enc(&tmT, CU_TENSOR_MAP_DATA_TYPE_BFLOAT16, 2, d_in[1], dims, st, box, es, CU_TENSOR_MAP_INTERLEAVE_NONE,
        CU_TENSOR_MAP_SWIZZLE_128B, CU_TENSOR_MAP_L2_PROMOTION_NONE, CU_TENSOR_MAP_FLOAT_OOB_FILL_NONE);
  }
  GPtr gp;
  gp.zero = 0;
  cudaGetSymbolAddress((void**)&gp.s, g_scratch);
  cudaGetSymbolAddress((void**)&gp.tab, g_slot_tab);
  cudaFuncSetAttribute(xdeepfm_kernel, cudaFuncAttributeMaxDynamicSharedMemorySize, SMEM_BYTES);
  xdeepfm_kernel<<<GRID, 384, SMEM_BYTES, cudaStreamPerThread>>>(
      (const int*)d_in[0], (const __nv_bfloat16*)d_in[1], (const __nv_bfloat16*)d_in[4], (const __nv_bfloat16*)d_in[5],
      (const __nv_bfloat16*)d_in[6], (const __nv_bfloat16*)d_in[2], (const __nv_bfloat16*)d_in[3],
      (const __nv_bfloat16*)d_in[7], (__nv_bfloat16*)d_out, gp, tmW, tmT);
}
```

```cpp
#include <cuda_runtime.h>
#include <cuda_bf16.h>
#include <cuda.h>
#include <stdint.h>

template <int TB = 1>
__device__ __forceinline__ void wgmma_ss_n256(float (&d)[96], float (&e)[32], uint64_t descA, uint64_t descB, int scaleD) {
  asm volatile("{\n.reg .pred p;\nsetp.ne.b32 p, %130, 0;\n"
      "wgmma.mma_async.sync.aligned.m64n256k16.f32.bf16.bf16 {"
      "%0, %1, %2, %3, %4, %5, %6, %7, %8, %9, %10, %11, %12, %13, %14, %15,"
      "%16, %17, %18, %19, %20, %21, %22, %23, %24, %25, %26, %27, %28, %29, %30, %31,"
      "%32, %33, %34, %35, %36, %37, %38, %39, %40, %41, %42, %43, %44, %45, %46, %47,"
      "%48, %49, %50, %51, %52, %53, %54, %55, %56, %57, %58, %59, %60, %61, %62, %63,"
      "%64, %65, %66, %67, %68, %69, %70, %71, %72, %73, %74, %75, %76, %77, %78, %79,"
      "%80, %81, %82, %83, %84, %85, %86, %87, %88, %89, %90, %91, %92, %93, %94, %95,"
      "%96, %97, %98, %99, %100, %101, %102, %103, %104, %105, %106, %107, %108, %109, %110, %111,"
      "%112, %113, %114, %115, %116, %117, %118, %119, %120, %121, %122, %123, %124, %125, %126, %127"
      "}, %128, %129, p, 1, 1, 0, %131;\n}\n"
      : "+f"(d[0]), "+f"(d[1]), "+f"(d[2]), "+f"(d[3]), "+f"(d[4]), "+f"(d[5]), "+f"(d[6]), "+f"(d[7]),
        "+f"(d[8]), "+f"(d[9]), "+f"(d[10]), "+f"(d[11]), "+f"(d[12]), "+f"(d[13]), "+f"(d[14]), "+f"(d[15]),
        "+f"(d[16]), "+f"(d[17]), "+f"(d[18]), "+f"(d[19]), "+f"(d[20]), "+f"(d[21]), "+f"(d[22]), "+f"(d[23]),
        "+f"(d[24]), "+f"(d[25]), "+f"(d[26]), "+f"(d[27]), "+f"(d[28]), "+f"(d[29]), "+f"(d[30]), "+f"(d[31]),
        "+f"(d[32]), "+f"(d[33]), "+f"(d[34]), "+f"(d[35]), "+f"(d[36]), "+f"(d[37]), "+f"(d[38]), "+f"(d[39]),
        "+f"(d[40]), "+f"(d[41]), "+f"(d[42]), "+f"(d[43]), "+f"(d[44]), "+f"(d[45]), "+f"(d[46]), "+f"(d[47]),
        "+f"(d[48]), "+f"(d[49]), "+f"(d[50]), "+f"(d[51]), "+f"(d[52]), "+f"(d[53]), "+f"(d[54]), "+f"(d[55]),
        "+f"(d[56]), "+f"(d[57]), "+f"(d[58]), "+f"(d[59]), "+f"(d[60]), "+f"(d[61]), "+f"(d[62]), "+f"(d[63]),
        "+f"(d[64]), "+f"(d[65]), "+f"(d[66]), "+f"(d[67]), "+f"(d[68]), "+f"(d[69]), "+f"(d[70]), "+f"(d[71]),
        "+f"(d[72]), "+f"(d[73]), "+f"(d[74]), "+f"(d[75]), "+f"(d[76]), "+f"(d[77]), "+f"(d[78]), "+f"(d[79]),
        "+f"(d[80]), "+f"(d[81]), "+f"(d[82]), "+f"(d[83]), "+f"(d[84]), "+f"(d[85]), "+f"(d[86]), "+f"(d[87]),
        "+f"(d[88]), "+f"(d[89]), "+f"(d[90]), "+f"(d[91]), "+f"(d[92]), "+f"(d[93]), "+f"(d[94]), "+f"(d[95]),
        "+f"(e[0]), "+f"(e[1]), "+f"(e[2]), "+f"(e[3]), "+f"(e[4]), "+f"(e[5]), "+f"(e[6]), "+f"(e[7]),
        "+f"(e[8]), "+f"(e[9]), "+f"(e[10]), "+f"(e[11]), "+f"(e[12]), "+f"(e[13]), "+f"(e[14]), "+f"(e[15]),
        "+f"(e[16]), "+f"(e[17]), "+f"(e[18]), "+f"(e[19]), "+f"(e[20]), "+f"(e[21]), "+f"(e[22]), "+f"(e[23]),
        "+f"(e[24]), "+f"(e[25]), "+f"(e[26]), "+f"(e[27]), "+f"(e[28]), "+f"(e[29]), "+f"(e[30]), "+f"(e[31])
      : "l"(descA), "l"(descB), "r"(scaleD), "n"(TB));
}
template <int TB = 1>
__device__ __forceinline__ void wgmma_ss_n192(float (&d)[96], uint64_t descA, uint64_t descB, int scaleD) {
  asm volatile("{\n.reg .pred p;\nsetp.ne.b32 p, %98, 0;\n"
      "wgmma.mma_async.sync.aligned.m64n192k16.f32.bf16.bf16 {"
      "%0, %1, %2, %3, %4, %5, %6, %7, %8, %9, %10, %11, %12, %13, %14, %15,"
      "%16, %17, %18, %19, %20, %21, %22, %23, %24, %25, %26, %27, %28, %29, %30, %31,"
      "%32, %33, %34, %35, %36, %37, %38, %39, %40, %41, %42, %43, %44, %45, %46, %47,"
      "%48, %49, %50, %51, %52, %53, %54, %55, %56, %57, %58, %59, %60, %61, %62, %63,"
      "%64, %65, %66, %67, %68, %69, %70, %71, %72, %73, %74, %75, %76, %77, %78, %79,"
      "%80, %81, %82, %83, %84, %85, %86, %87, %88, %89, %90, %91, %92, %93, %94, %95"
      "}, %96, %97, p, 1, 1, 0, %99;\n}\n"
      : "+f"(d[0]), "+f"(d[1]), "+f"(d[2]), "+f"(d[3]), "+f"(d[4]), "+f"(d[5]), "+f"(d[6]), "+f"(d[7]),
        "+f"(d[8]), "+f"(d[9]), "+f"(d[10]), "+f"(d[11]), "+f"(d[12]), "+f"(d[13]), "+f"(d[14]), "+f"(d[15]),
        "+f"(d[16]), "+f"(d[17]), "+f"(d[18]), "+f"(d[19]), "+f"(d[20]), "+f"(d[21]), "+f"(d[22]), "+f"(d[23]),
        "+f"(d[24]), "+f"(d[25]), "+f"(d[26]), "+f"(d[27]), "+f"(d[28]), "+f"(d[29]), "+f"(d[30]), "+f"(d[31]),
        "+f"(d[32]), "+f"(d[33]), "+f"(d[34]), "+f"(d[35]), "+f"(d[36]), "+f"(d[37]), "+f"(d[38]), "+f"(d[39]),
        "+f"(d[40]), "+f"(d[41]), "+f"(d[42]), "+f"(d[43]), "+f"(d[44]), "+f"(d[45]), "+f"(d[46]), "+f"(d[47]),
        "+f"(d[48]), "+f"(d[49]), "+f"(d[50]), "+f"(d[51]), "+f"(d[52]), "+f"(d[53]), "+f"(d[54]), "+f"(d[55]),
        "+f"(d[56]), "+f"(d[57]), "+f"(d[58]), "+f"(d[59]), "+f"(d[60]), "+f"(d[61]), "+f"(d[62]), "+f"(d[63]),
        "+f"(d[64]), "+f"(d[65]), "+f"(d[66]), "+f"(d[67]), "+f"(d[68]), "+f"(d[69]), "+f"(d[70]), "+f"(d[71]),
        "+f"(d[72]), "+f"(d[73]), "+f"(d[74]), "+f"(d[75]), "+f"(d[76]), "+f"(d[77]), "+f"(d[78]), "+f"(d[79]),
        "+f"(d[80]), "+f"(d[81]), "+f"(d[82]), "+f"(d[83]), "+f"(d[84]), "+f"(d[85]), "+f"(d[86]), "+f"(d[87]),
        "+f"(d[88]), "+f"(d[89]), "+f"(d[90]), "+f"(d[91]), "+f"(d[92]), "+f"(d[93]), "+f"(d[94]), "+f"(d[95])
      : "l"(descA), "l"(descB), "r"(scaleD), "n"(TB));
}
template <unsigned long long DESC, int SCALE>
__device__ __forceinline__ void wgmma_rs_n56(float (&d)[28], uint32_t a0, uint32_t a1, uint32_t a2, uint32_t a3) {
  asm volatile("{\n.reg .b64 desc;\nmov.b64 desc, %32;\n"
      "wgmma.mma_async.sync.aligned.m64n56k16.f32.bf16.bf16 {"
      "%0, %1, %2, %3, %4, %5, %6, %7, %8, %9, %10, %11, %12, %13, %14, %15,"
      "%16, %17, %18, %19, %20, %21, %22, %23, %24, %25, %26, %27"
      "}, {%28, %29, %30, %31}, desc, %33, 1, 1, 0;\n}\n"
      : "+f"(d[0]), "+f"(d[1]), "+f"(d[2]), "+f"(d[3]), "+f"(d[4]), "+f"(d[5]), "+f"(d[6]), "+f"(d[7]),
        "+f"(d[8]), "+f"(d[9]), "+f"(d[10]), "+f"(d[11]), "+f"(d[12]), "+f"(d[13]), "+f"(d[14]), "+f"(d[15]),
        "+f"(d[16]), "+f"(d[17]), "+f"(d[18]), "+f"(d[19]), "+f"(d[20]), "+f"(d[21]), "+f"(d[22]), "+f"(d[23]),
        "+f"(d[24]), "+f"(d[25]), "+f"(d[26]), "+f"(d[27])
      : "r"(a0), "r"(a1), "r"(a2), "r"(a3), "n"(DESC), "n"(SCALE));
}
template <unsigned long long DESC, int SCALE>
__device__ __forceinline__ void wgmma_rs_n32(float (&d)[28], uint32_t a0, uint32_t a1, uint32_t a2, uint32_t a3) {
  asm volatile("{\n.reg .b64 desc;\nmov.b64 desc, %20;\n"
      "wgmma.mma_async.sync.aligned.m64n32k16.f32.bf16.bf16 {"
      "%0, %1, %2, %3, %4, %5, %6, %7, %8, %9, %10, %11, %12, %13, %14, %15"
      "}, {%16, %17, %18, %19}, desc, %21, 1, 1, 0;\n}\n"
      : "+f"(d[0]), "+f"(d[1]), "+f"(d[2]), "+f"(d[3]), "+f"(d[4]), "+f"(d[5]), "+f"(d[6]), "+f"(d[7]),
        "+f"(d[8]), "+f"(d[9]), "+f"(d[10]), "+f"(d[11]), "+f"(d[12]), "+f"(d[13]), "+f"(d[14]), "+f"(d[15])
      : "r"(a0), "r"(a1), "r"(a2), "r"(a3), "n"(DESC), "n"(SCALE));
}

constexpr int NB = 4096, NF = 26, DIN = 1664;
constexpr int NGEMM = 128, NEXTRA = 4, GRID = NGEMM + NEXTRA;
constexpr int NC_EXTRA = 84;
constexpr int NC_WG0 = 16;
constexpr int WK = 1;
constexpr int OB = 5;
constexpr int HK = 3;
constexpr int PE0 = 14;
constexpr int WD = 2;
constexpr int GI = 3;
constexpr int PE1 = 6;
constexpr int PE2 = 12;
constexpr int PS2 = 11;
constexpr int PS = 6;
constexpr int RB = 4;
constexpr int NC_GEMM = 29, NBIG = NB - NGEMM * NC_GEMM - NEXTRA * NC_EXTRA;
static_assert(NBIG >= 0 && NBIG <= NGEMM && NC_EXTRA % 2 == 0 && NC_EXTRA <= 92 && NC_WG0 <= 17 && NC_WG0 >= 15, "split");
constexpr int CW_MAIN = 22 * 1792, CW_LIN = 2 * 1024, CW_BYTES = CW_MAIN + CW_LIN;
constexpr int XSLOT = 4096;

constexpr int UNIT = 8192, FS = 18;
constexpr int U_W = 6, U_XB = 18, U_SP = 24;
constexpr int CW_CUT = 9;
constexpr int OFF_CW = 0, OFF_CW2 = 6 * UNIT, OFF_CWL = 9 * UNIT;
constexpr int OFF_PART = OFF_CWL + CW_LIN;
constexpr int CROW = 528;
constexpr int OFF_CIN = 2 * UNIT;
constexpr int OFF_GIDX = 26 * UNIT;
constexpr int OFF_TIDX = OFF_GIDX + 128 * NF * 4 - 8 * 64 * 4;
constexpr int OFF_CIDX = OFF_GIDX + 128 * NF * 4;
constexpr int OFF_EPI = OFF_CIDX + 30 * NF * 4;
constexpr int OFF_DNN = OFF_EPI + 128 * 16;
constexpr int OFF_BAR = OFF_DNN + 96 * 4;
constexpr int SMEM_BYTES = OFF_BAR + 66 * 8;
static_assert(CW_CUT * 1792 <= 2 * UNIT && (22 - CW_CUT) * 1792 <= 3 * UNIT && 30 * CROW <= 2 * UNIT, "smem");
constexpr uint32_t SMEM_BASE = 1024;
static_assert(SMEM_BYTES <= 232448, "smem");
static_assert(OFF_EPI % 16 == 0 && OFF_CIDX % 16 == 0 && OFF_BAR % 8 == 0, "align");
constexpr int XOFF_W3 = 0, XOFF_W2 = 35152, XOFF_W1 = 70304, XOFF_M = XOFF_W1 + 8 * 1352, XOFF_S = XOFF_M + 32 * 40 * 4,
              XOFF_SLOT = 10 * UNIT, XOFF_CIN0 = 2 * UNIT, XOFF_CIN1 = 18 * UNIT, XOFF_CIDX = 22 * UNIT;
static_assert(XOFF_S + 14 * 3136 <= 21 * UNIT && 46 * CROW <= 3 * UNIT, "smem");

constexpr int BAR_FULL = 8,
              BAR_EV = 16,
              BAR_CW = 24,
              BAR_GIDX = 25, BAR_CIDX = 26,
              BAR_W0 = 27,
              BAR_DNN = 28,
              BAR_T = 29,
              BAR_GDONE = 30,
              BAR_PART = 31,
              BAR_CFULL = 32,
              BAR_C0 = 64;
constexpr int EV_CW = 29, EV_CIN = 30, EV_SLOT = 31, EV_END = 33;
__device__ __forceinline__ uint32_t ev_bar(uint32_t bars, int e) { return bars + 8 * (BAR_EV + (e & 7)); }
__device__ __forceinline__ uint32_t ev_par(int e) { return (e >> 3) & 1; }
__host__ __device__ constexpr int b_x(int t) { return ((0xb2c1430bu >> (4 * t)) & 15) * 2; }
__host__ __device__ constexpr int b_w(int t) { return (0x0d0a120eu >> (8 * (t & 3))) & 31; }
__host__ __device__ constexpr int b_ws(int t) { return (t & 3) == 3 ? 4 : 1; }

struct Scratch {
  uint4 cw[CW_BYTES / 16];
  float part[8 * NB];
  unsigned dflag[16 * 8];
  unsigned epoch[GRID];
  unsigned foldflag;
};
__device__ __align__(128) Scratch g_scratch;
struct GPtr { Scratch* s; const uint4* tab; const uint4* jobs; uint32_t zero; };

__device__ __forceinline__ void wg_fence() { asm volatile("wgmma.fence.sync.aligned;" ::: "memory"); }
__device__ __forceinline__ void wg_commit() { asm volatile("wgmma.commit_group.sync.aligned;" ::: "memory"); }
template <int N> __device__ __forceinline__ void wg_wait() { asm volatile("wgmma.wait_group.sync.aligned %0;" ::"n"(N) : "memory"); }
__device__ __forceinline__ uint64_t mkdesc(uint32_t addr, uint32_t lbo, uint32_t sbo, uint32_t swz) {
  return (uint64_t)((addr & 0x3FFFF) >> 4) | ((uint64_t)(lbo >> 4) << 16) | ((uint64_t)(sbo >> 4) << 32) | ((uint64_t)swz << 62);
}
__device__ __forceinline__ bool elect1() {
  uint32_t p; asm volatile("{\n.reg .pred p;\nelect.sync _|p, 0xffffffff;\nselp.b32 %0, 1, 0, p;\n}" : "=r"(p)); return p;
}
__device__ __forceinline__ int fresh(int v) { asm volatile("" : "+r"(v)); return v; }
__device__ __forceinline__ void sched_fence() { asm volatile("pmevent 0;" ::: "memory"); }
__device__ __forceinline__ void mbar_init(uint32_t bar, uint32_t cnt) { asm volatile("mbarrier.init.shared::cta.b64 [%0], %1;" ::"r"(bar), "r"(cnt) : "memory"); }
__device__ __forceinline__ void mbar_arrive(uint32_t bar) { asm volatile("mbarrier.arrive.shared::cta.b64 _, [%0];" ::"r"(bar) : "memory"); }
__device__ __forceinline__ void mbar_arrive_cta(uint32_t bar, uint32_t cta) {
  asm volatile("{\n.reg .b32 r;\nmapa.shared::cluster.u32 r, %0, %1;\nmbarrier.arrive.shared::cluster.b64 _, [r];\n}" ::"r"(bar), "r"(cta) : "memory");
}
__device__ __forceinline__ void mbar_expect_tx(uint32_t bar, uint32_t bytes) { asm volatile("mbarrier.arrive.expect_tx.shared::cta.b64 _, [%0], %1;" ::"r"(bar), "r"(bytes) : "memory"); }
__device__ __forceinline__ void mbar_wait(uint32_t bar, uint32_t parity) {
  asm volatile("{\n.reg .pred p;\nLAB_WAIT:\nmbarrier.try_wait.parity.shared::cta.b64 p, [%0], %1;\n@!p bra LAB_WAIT;\n}" ::"r"(bar), "r"(parity) : "memory");
}
__device__ __forceinline__ void flag_wait(const unsigned* p, unsigned target, unsigned sleep_ns) {
  asm volatile("{\n.reg .pred p;\n.reg .u32 n, v;\nmov.u32 n, 0;\nLAB_WAIT:\n"
               "ld.acquire.gpu.global.u32 v, [%0];\n"
               "sub.u32 v, v, %1;\n"
               "setp.ge.s32 p, v, 0;\n"
               "@p bra DONE;\n"
               "nanosleep.u32 %2;\n"
               "add.u32 n, n, 1;\n"
               "setp.lt.u32 p, n, 400000;\n"
               "@p bra LAB_WAIT;\n"
               "DONE:\n}" ::"l"(p), "r"(target), "r"(sleep_ns) : "memory");
}
__device__ __forceinline__ void flag_add(unsigned* p) { asm volatile("red.release.gpu.global.add.u32 [%0], 1;" ::"l"(p) : "memory"); }
__device__ __forceinline__ void tma_load(uint32_t dst, const CUtensorMap* tm, int c0, int c1, uint32_t bar) {
  asm volatile("cp.async.bulk.tensor.2d.shared::cluster.global.mbarrier::complete_tx::bytes [%0], [%1, {%3, %4}], [%2];"
               ::"r"(dst), "l"(tm), "r"(bar), "r"(c0), "r"(c1) : "memory");
}
__device__ __forceinline__ void tma_row_mc(uint32_t dst, const CUtensorMap* tm, int row, uint32_t bar) {
  asm volatile("cp.async.bulk.tensor.2d.shared::cluster.global.mbarrier::complete_tx::bytes.multicast::cluster [%0], [%1, {%3, %4}], [%2], %5;"
               ::"r"(dst), "l"(tm), "r"(bar), "r"(0), "r"(row), "h"((uint16_t)3));
}
__device__ __forceinline__ void tma_row(uint32_t dst, const CUtensorMap* tm, int row, uint32_t bar) {
  asm volatile("cp.async.bulk.tensor.2d.shared::cluster.global.mbarrier::complete_tx::bytes [%0], [%1, {%3, %4}], [%2];"
               ::"r"(dst), "l"(tm), "r"(bar), "r"(0), "r"(row));
}
__device__ __forceinline__ void bulk_load(uint32_t dst, const void* src, uint32_t bytes, uint32_t bar) {
  asm volatile("cp.async.bulk.shared::cluster.global.mbarrier::complete_tx::bytes [%0], [%1], %2, [%3];"
               ::"r"(dst), "l"(src), "r"(bytes), "r"(bar));
}
__device__ __forceinline__ void l2_prefetch(const void* src, uint32_t bytes) {
  asm volatile("cp.async.bulk.prefetch.L2.global [%0], %1;" ::"l"(src), "r"(bytes));
}
__device__ __forceinline__ void w_prefetch(const __nv_bfloat16* w1, int f, int cta, int piece) {
  l2_prefetch(w1 + (f * 64 + (cta >> 3) * 4 + (cta & 1) * 2 + (piece & 1)) * DIN + (piece < 2 ? (cta & 6) * 192 : 1536 + (cta & 4) * 16),
              piece < 2 ? 768 : 128);
}
__device__ __forceinline__ void cpasync16(uint32_t dst, const void* src) {
  asm volatile("cp.async.cg.shared.global [%0], [%1], 16;" ::"r"(dst), "l"(src) : "memory");
}
template <int ID, int N> __device__ __forceinline__ void bar_sync() { asm volatile("bar.sync %0, %1;" ::"n"(ID), "n"(N) : "memory"); }
template <int ID, int N> __device__ __forceinline__ void bar_arrive() { asm volatile("bar.arrive %0, %1;" ::"n"(ID), "n"(N) : "memory"); }
__device__ __forceinline__ void ldsm4t(uint32_t& a, uint32_t& b, uint32_t& c, uint32_t& d, uint32_t addr) {
  asm volatile("ldmatrix.sync.aligned.m8n8.x4.trans.shared.b16 {%0,%1,%2,%3}, [%4];" : "=r"(a), "=r"(b), "=r"(c), "=r"(d) : "r"(addr) : "memory");
}
__device__ __forceinline__ void ldsm2t(uint32_t& a, uint32_t& b, uint32_t addr) {
  asm volatile("ldmatrix.sync.aligned.m8n8.x2.trans.shared.b16 {%0,%1}, [%2];" : "=r"(a), "=r"(b) : "r"(addr) : "memory");
}
__device__ __forceinline__ int lds32(uint32_t addr) { int v; asm volatile("ld.shared.b32 %0, [%1];" : "=r"(v) : "r"(addr)); return v; }
__device__ __forceinline__ int2 lds64(uint32_t addr) { int2 v; asm volatile("ld.shared.v2.b32 {%0,%1}, [%2];" : "=r"(v.x), "=r"(v.y) : "r"(addr)); return v; }
__device__ __forceinline__ int4 lds128(uint32_t addr) {
  int4 v; asm volatile("ld.shared.v4.b32 {%0,%1,%2,%3}, [%4];" : "=r"(v.x), "=r"(v.y), "=r"(v.z), "=r"(v.w) : "r"(addr)); return v;
}
__device__ __forceinline__ float4 lds128f(uint32_t addr) {
  float4 v; asm volatile("ld.shared.v4.f32 {%0,%1,%2,%3}, [%4];" : "=f"(v.x), "=f"(v.y), "=f"(v.z), "=f"(v.w) : "r"(addr) : "memory"); return v;
}
__device__ __forceinline__ void sts32f(uint32_t addr, float v) { asm volatile("st.shared.f32 [%0], %1;" ::"r"(addr), "f"(v) : "memory"); }
__device__ __forceinline__ float bf_lo(uint32_t v) { return __uint_as_float(v << 16); }
__device__ __forceinline__ float bf_hi(uint32_t v) { return __uint_as_float(v & 0xffff0000u); }
__device__ __forceinline__ float bf2f(__nv_bfloat16 v) { return __bfloat162float(v); }

__device__ __forceinline__ uint32_t mul2(uint32_t a, uint32_t b) {
  uint32_t r; asm volatile("mul.rn.bf16x2 %0, %1, %2;" : "=r"(r) : "r"(a), "r"(b)); return r;
}
__device__ __forceinline__ uint32_t mul2lo(uint32_t a, uint32_t b) {
  uint32_t r;
  asm volatile("{\n.reg .b16 l, h;\n.reg .b32 t;\nmov.b32 {l, h}, %2;\nmov.b32 t, {l, l};\nmul.rn.bf16x2 %0, %1, t;\n}" : "=r"(r) : "r"(a), "r"(b));
  return r;
}
__device__ __forceinline__ uint32_t mul2hi(uint32_t a, uint32_t b) {
  uint32_t r;
  asm volatile("{\n.reg .b16 l, h;\n.reg .b32 t;\nmov.b32 {l, h}, %2;\nmov.b32 t, {h, h};\nmul.rn.bf16x2 %0, %1, t;\n}" : "=r"(r) : "r"(a), "r"(b));
  return r;
}

__host__ __device__ constexpr int xfield(int r, int e, int c) {
  return r == 9 ? 24 + e : 8 * (r / 3) + 2 * (((r % 3) + c) & 3) + (((r % 3) == 2 && c >= 2) ? 1 - e : e);
}
__host__ __device__ constexpr int blk_a(int b) { return b < 12 ? 3 * (b / 8) + ((b & 3) == 3) : (b < 15 ? 3 * (b - 12) : 3 * (b - 15)); }
__host__ __device__ constexpr int blk_b(int b) { return b < 12 ? 3 * (b < 4 ? 1 : 2) + ((b & 3) == 3 ? 0 : (b & 3)) : (b < 15 ? 3 * (b - 12) + 1 : 9); }
__host__ __device__ constexpr int slot_pq(int u, int e, int c) {
  return u < 36 ? (xfield(blk_a(u >> 1), e, c) | (xfield(blk_b(u >> 1), u & 1, c) << 8))
       : u < 39 ? (xfield(3 * (u - 36), e, c) | (xfield(3 * (u - 36), 0, c) << 8))
       : u < 42 ? (xfield(3 * (u - 39), e, c) | (xfield(3 * (u - 39) + 2, e, c) << 8))
       : u == 42 ? (xfield(3 * e, 1, c) * 257)
       : u == 43 ? (e == 0 ? (xfield(6, 1, c) * 257)
                           : (c == 0 ? 24 * 257 : c == 1 ? 25 * 257 : c == 2 ? (24 | 25 << 8) : 26 * 257))
       : u < 47 ? (xfield(3 * (u - 44), e, c) | (26 << 8))
       : (c == 0 ? ((24 + e) | 26 << 8) : c == 3 ? ((26 + e) | (27 - e) << 8) : 27 * 257);
}
struct SlotTab { uint32_t v[48 * 8]; };
constexpr SlotTab make_slot_tab() {
  SlotTab t{};
  for (int u = 0; u < 48; u++)
    for (int k = 0; k < 8; k++) {
      const int pq = slot_pq(u, k & 1, k >> 1), p = pq & 255, q = pq >> 8;
      t.v[u * 8 + k] = (uint32_t)((p * 28 + q) * 4) | ((uint32_t)(((p != q && q < 26) ? q * 28 + p : 27 * 28 + 27) * 4) << 16);
    }
  return t;
}
__device__ __align__(16) const SlotTab g_slot_tab = make_slot_tab();

struct CinCtx {
  uint32_t tab0, tab1, full, fmask, it, lim, co, sb;
  uint32_t cin, o03, o14, o25, o9, o78, selA, selB;
  bool ones, lead;
};
constexpr unsigned long long CW_DESC = (unsigned long long)((SMEM_BASE + OFF_CW) >> 4) | (8ull << 16) | (16ull << 32);
constexpr int OFF_INIT = U_SP * UNIT;
constexpr unsigned long long INIT_DESC = (unsigned long long)((SMEM_BASE + OFF_INIT) >> 4) | (9ull << 32);
constexpr unsigned long long ONES_DESC = (SMEM_BASE + OFF_INIT + 4608) >> 4;
constexpr unsigned long long CWL_DESC = CW_DESC + (OFF_CWL - OFF_CW) / 16;

template <int U>
__device__ __forceinline__ uint32_t zreg(uint32_t (&x)[11][2], int h, const CinCtx& c) {
  if constexpr (U < 36) {
    if constexpr (U & 1) return mul2hi(x[blk_a(U >> 1)][h], x[blk_b(U >> 1)][h]);
    else return mul2lo(x[blk_a(U >> 1)][h], x[blk_b(U >> 1)][h]);
  } else if constexpr (U < 39) {
    return mul2lo(x[3 * (U - 36)][h], x[3 * (U - 36)][h]);
  } else if constexpr (U < 42) {
    return mul2(x[3 * (U - 39)][h], x[3 * (U - 39) + 2][h]);
  } else if constexpr (U == 42) {
    const uint32_t p = __byte_perm(x[0][h], x[3][h], 0x7632);
    return mul2(p, p);
  } else {
    x[10][h] = c.ones ? 0x3f803f80u : x[9][h];
    return mul2(__byte_perm(x[6][h], x[10][h], c.selA), __byte_perm(x[6][h], x[10][h], c.selB));
  }
}

__host__ __device__ constexpr int kord(int s) { return s == 0 ? 21 : s < 4 ? 14 + s : s < 19 ? s - 4 : s - 1; }
template <int S0, int NS>
struct ZGroup {
  uint32_t z[NS][4];
  template <int I = 0>
  __device__ __forceinline__ void fill(uint32_t (&x)[11][2], const CinCtx& c) {
    if constexpr (I < NS) {
      z[I][0] = zreg<2 * kord(S0 + I)>(x, 0, c);
      z[I][1] = zreg<2 * kord(S0 + I)>(x, 1, c);
      z[I][2] = zreg<2 * kord(S0 + I) + 1>(x, 0, c);
      z[I][3] = zreg<2 * kord(S0 + I) + 1>(x, 1, c);
      fill<I + 1>(x, c);
    }
  }
  template <int I = 0>
  __device__ __forceinline__ void mma(float (&acc)[28]) {
    if constexpr (I < NS) {
      constexpr int S = kord(S0 + I);
      wgmma_rs_n56<CW_DESC + (S < CW_CUT ? S * 1792 : OFF_CW2 - OFF_CW + (S - CW_CUT) * 1792) / 16, (S0 + I) != 0>(acc, z[I][0], z[I][1], z[I][2], z[I][3]);
      mma<I + 1>(acc);
    }
  }
};

__device__ __forceinline__ void cin_finish(const CinCtx& c, float (&acc)[28], uint32_t out) {
#pragma unroll
  for (int i = 0; i < 28; i++) asm volatile("" : "+f"(acc[i]));
  float s0 = acc[12] * acc[13], s1 = acc[14] * acc[15];
#pragma unroll
  for (int i = 0; i < 12; i += 2) {
    s0 = fmaf(acc[i], acc[16 + i], s0);
    s1 = fmaf(acc[i + 1], acc[17 + i], s1);
  }
  sts32f(out, s0 + s1);
}

__device__ __forceinline__ void cin_ldsm(const CinCtx& c, uint32_t so, uint32_t (&x)[11][2], int i) {
  if (i == 0) ldsm4t(x[0][0], x[0][1], x[3][0], x[3][1], so + c.o03);
  if (i == 1) ldsm2t(x[6][0], x[6][1], so + c.o03 + 2048);
  if (i == 1) ldsm2t(x[9][0], x[9][1], so + c.o9 + 3072);
  if (i == 2) ldsm4t(x[1][0], x[1][1], x[4][0], x[4][1], so + c.o14);
  if (i == 3) ldsm4t(x[2][0], x[2][1], x[5][0], x[5][1], so + c.o25);
  if (i == 4) ldsm4t(x[7][0], x[7][1], x[8][0], x[8][1], so + c.o78 + 2048);
}
__device__ __forceinline__ bool cin_late(const CinCtx& c, int k) {
  uint32_t ok = 1;
  asm volatile("{\n.reg .pred p;\nmbarrier.test_wait.parity.shared::cta.b64 p, [%1], %2;\nselp.b32 %0, 1, 0, p;\n}"
               : "=r"(ok) : "r"(c.full + (c.it & c.fmask) + 8 * k), "r"((((c.it & ~c.fmask) << 25) ^ (c.lim - 9 - 8 * k - c.it)) >> 31) : "memory");
  return !ok;
}
__device__ __forceinline__ void cin_load(const CinCtx& c, int k, bool late, uint32_t (&x)[11][2]) {
  const uint32_t fb = c.full + (c.it & c.fmask) + 8 * k;
  if (__builtin_expect(late, 0)) mbar_wait(fb, ((c.it & ~c.fmask) >> 6) & 1);
#pragma unroll
  for (int i = 0; i < 5; i++) cin_ldsm(c, c.sb + (c.tab0 & 31) * UNIT + k * XSLOT, x, i);
  if (c.lead) mbar_arrive(fb + 64);
}
__device__ __forceinline__ void cin_advance(CinCtx& c) {
  const uint32_t t = __funnelshift_r(c.tab0, c.tab1, 8);
  c.tab1 = __funnelshift_r(c.tab1, c.tab0, 8);
  c.tab0 = t;
  c.it += 16;
  c.co += 2 * CROW;
}
constexpr int CG_SIZE = 2;
constexpr int CG_WAIT = 4;
constexpr int CG_HEAD = 4;
constexpr int CG_LOAD = 4;
constexpr int CG_N = (22 + CG_SIZE - 1) / CG_SIZE;
constexpr int CG_ASK = 4;
constexpr int CG_HW = 3;
template <int G, int GEND>
__device__ __forceinline__ void cin_groups(const CinCtx& c, uint32_t (&x)[11][2], float (&acc)[28],
                                           int q, bool& late, uint32_t (&xn)[11][2]) {
  if constexpr (G < GEND) {
    constexpr int S0 = G * CG_SIZE, NS = (S0 + CG_SIZE <= 22) ? CG_SIZE : 22 - S0;
    if constexpr (G == CG_ASK) late = cin_late(c, q);
    ZGroup<S0, NS> g; g.fill(x, c);
    wg_fence();
    g.mma(acc);
    wg_commit();
    if constexpr (G == CG_N - 1) {
      wg_fence();
      wgmma_rs_n32<CWL_DESC, 1>(acc, x[0][0], x[0][1], x[3][0], x[3][1]);
      wgmma_rs_n32<CWL_DESC + 1024 / 16, 1>(acc, x[6][0], x[6][1], x[10][0], x[10][1]);
      wg_commit();
    }
    if constexpr (G == CG_LOAD) cin_load(c, q, late, xn);
    if constexpr (G != CG_HEAD - 1) {
      if constexpr (G == CG_N - 1 || G < CG_HW) wg_wait<CG_WAIT + 1>(); else wg_wait<CG_WAIT>();
    }
    cin_groups<G + 1, GEND>(c, x, acc, q, late, xn);
  }
}
__device__ __forceinline__ void cin_head(const CinCtx& c, uint32_t (&x)[11][2], float (&acc)[28], int q, bool& late) {
  cin_groups<0, CG_HEAD>(c, x, acc, q, late, x);
}
__device__ __forceinline__ void cin_tail(const CinCtx& c, uint32_t (&x)[11][2], float (&acc)[28],
                                         int q, bool& late, uint32_t (&xn)[11][2]) {
  cin_groups<CG_HEAD, CG_N>(c, x, acc, q, late, xn);
}

__device__ __forceinline__ void cin_setup(CinCtx& c, uint32_t sb, int wg, int tid, bool gemm, int nj) {
  c.tab0 = !gemm ? 0x0d0c0b0a + wg * 0x04040404 : wg ? 0x0d0c0b0a : 0x100f0e1a;
  c.tab1 = !gemm ? c.tab0 : wg ? 0x17171615 : 0x14131211;
  c.full = sb + OFF_BAR + 8 * (BAR_CFULL + wg * 16);
  c.fmask = gemm ? 0x70 : 0x30;
  c.it = 0; c.lim = 8 * nj; c.sb = sb;
  c.lead = (tid & 31) == 0 && !gemm;
  const uint32_t f0 = tid & 7, ch = (tid & 0x60) | ((tid & 8) << 1), chm = ch | ((tid & 16) << 6);
  c.o03 = (f0 * 144) ^ chm;
  c.o14 = (((f0 + 2) & 7) * 144) ^ chm;
  c.o25 = c.o03 ^ (tid & 4 ? 5 * 144 : 4 * 144);
  c.o9 = ((tid & 1) * 144) ^ ch;
  c.o78 = tid & 16 ? c.o25 - 1024 : c.o14;
  const int q = tid & 3;
  c.selA = q == 1 ? 0x7632 : 0x5432;
  c.selB = q == 0 ? 0x5432 : 0x7632;
  c.ones = q == 3;
}
template <typename F0, typename F, typename F2>
__device__ __forceinline__ void cin_run(CinCtx& c, F0 first_load, F after_start, F2 before_end) {
  float accA[28], accB[28];
  uint32_t xA[11][2], xB[11][2];
  first_load(xA);
  bool late;
  cin_head(c, xA, accA, 0, late);
  after_start();
#pragma unroll 1
  for (;;) {
    const uint32_t out = c.cin + c.co;
    cin_tail(c, xA, accA, 0, late, xB);
    if (c.it + 8 >= c.lim) { before_end(); wg_wait<0>(); cin_finish(c, accA, out); break; }
    cin_head(c, xB, accB, 1, late);
    wg_wait<CG_HEAD>();
    cin_finish(c, accA, out);
    cin_tail(c, xB, accB, 1, late, xA);
    cin_advance(c);
    if (c.it >= c.lim) { before_end(); wg_wait<0>(); cin_finish(c, accB, out + CROW); break; }
    cin_head(c, xA, accA, 0, late);
    wg_wait<CG_HEAD>();
    cin_finish(c, accB, out + CROW);
  }
}

constexpr float ALPHA = 0.3292034911525734f, KAPPA = 2.423681954311584f;

constexpr int GD = 1;
constexpr int GK = 0;
constexpr int TK = 2;
constexpr int GL = 2;
template <int NG>
struct Gelu {
  float4 q[NG / 2];
  float u[4 * NG];
  float ab;
  uint32_t ep;
  static constexpr int END = NG + GD + 4;
  __device__ __forceinline__ void start(uint32_t a, uint32_t sb) {
    ep = a;
    ab = __int_as_float(lds32(sb + OFF_EPI + 1024));
  }
  __device__ __forceinline__ void take(const Gelu& o) {
#pragma unroll
    for (int m = TK; m < NG / 2; m++)
      asm volatile("mov.b32 %0, %4;\nmov.b32 %1, %5;\nmov.b32 %2, %6;\nmov.b32 %3, %7;"
                   : "=f"(q[m].x), "=f"(q[m].y), "=f"(q[m].z), "=f"(q[m].w) : "f"(o.q[m].x), "f"(o.q[m].y), "f"(o.q[m].z), "f"(o.q[m].w));
    ab = o.ab;
  }
  struct Nop { __device__ __forceinline__ void operator()(int) const {} };
  template <int I0, int I1, bool LOAD = true, typename F = Nop>
  __device__ __forceinline__ void part(float (&d)[4 * NG], float& r0, float& r1, F hook = F()) {
#pragma unroll
    for (int i = I0; i < I1; i++) {
      sched_fence();
      hook(i - I0);
#pragma unroll
      for (int m = 0; m < NG / 2; m++)
        if ((LOAD || m < TK) && i == 2 * m + GD + 4 - (m < 2 ? 2 : GL)) q[m] = lds128f(ep + m * 64);
#pragma unroll
      for (int e = 0; e < 4; e++) {
        const int k0 = 4 * i + e, k1 = k0 - 4, k2 = k0 - 8, k3 = k0 - 12, k4 = k3 - 4 * GD, k5 = k4 - 4;
        if (k3 >= 0 && k3 < 4 * NG) asm volatile("tanh.approx.f32 %0, %0;" : "+f"(u[k3]));
        if (k5 >= 0) {
          const float4 v = q[k5 >> 3];
          float& r = e & 2 ? r1 : r0;
          asm volatile("fma.rn.f32 %0, %1, %2, %0;" : "+f"(r) : "f"(d[k5]), "f"(k5 & 4 ? (e & 1 ? v.w : v.z) : (e & 1 ? v.y : v.x)));
        }
        if (k4 >= 0 && k4 < 4 * NG) asm volatile("fma.rn.f32 %0, %0, %1, %0;" : "+f"(d[k4]) : "f"(u[k4]));
        if (k2 >= 0 && k2 < 4 * NG) asm volatile("mul.rn.f32 %0, %0, %1;" : "+f"(u[k2]) : "f"(d[k2]));
        if (k1 >= 0 && k1 < 4 * NG) asm volatile("fma.rn.f32 %0, %1, %1, %2;" : "=f"(u[k1]) : "f"(d[k1]), "f"(KAPPA));
        if (k0 < 4 * NG) asm volatile("fma.rn.f32 %0, %0, %1, %2;" : "+f"(d[k0]) : "f"(ALPHA), "f"(ab));
      }
    }
    sched_fence();
  }
};
__device__ __forceinline__ void pin(float a, float b, uint32_t addr, uint32_t zero) {
  asm volatile("{\n.reg .pred p;\nsetp.ne.u32 p, %3, 0;\n@p st.shared.v2.f32 [%0], {%1, %2};\n}" ::"r"(addr), "f"(a), "f"(b), "r"(zero) : "memory");
}
__device__ __forceinline__ void hand_on(float (&d)[96], const float (&s)[96]) {
#pragma unroll
  for (int i = 0; i < 96; i++) asm volatile("mov.b32 %0, %1;" : "=f"(d[i]) : "f"(s[i]));
}
__device__ __forceinline__ uint64_t desc_x(int u) { return mkdesc(SMEM_BASE, 16, 1024, 1) + u * (UNIT / 16); }
__device__ __forceinline__ uint64_t desc_w(int u, int stride = 1) { return mkdesc(SMEM_BASE, stride * UNIT, 1024, 1) + u * (UNIT / 16); }
__device__ __forceinline__ void tile_step(float (&d)[96], uint64_t dA, uint64_t dB) {
  wg_fence();
#pragma unroll
  for (int k = 0; k < 4; k++) wgmma_ss_n192(d, dA + 2 * k, dB + 128 * k, 1);
  wg_commit();
}
template <int K0 = 0, int K1 = 4>
__device__ __forceinline__ void wide_step(float (&d)[96], float (&e)[32], uint64_t dA, uint64_t dB) {
  wg_fence();
#pragma unroll
  for (int k = K0; k < K1; k++) wgmma_ss_n256(d, e, dA + 2 * k, dB + 128 * k, 1);
  wg_commit();
}
constexpr int slot_of(int wg, int j) {
  return wg ? (j == 0 ? 24 * UNIT : j <= 8 ? 10 * UNIT + (j - 1) * XSLOT : 21 * UNIT + (j - 9) * XSLOT)
            : (j == 0 ? OFF_GIDX + 2 * XSLOT : (j < 3 ? OFF_GIDX + 2 * XSLOT : 14 * UNIT) + (j - 3) * XSLOT);
}
constexpr int NLW = 3;
constexpr int NE = 10;
constexpr int LB = 1;
struct alignas(8) Job { uint32_t wait, par, slot, full, idx, next; };
struct JobTab { Job v[30 + NC_EXTRA]; };
constexpr Job make_job(int wait, int par, int slot, int full, int sample, int next) {
  return Job{uint32_t(OFF_BAR + 8 * wait), uint32_t(par), uint32_t(slot), uint32_t(OFF_BAR + 8 * full), uint32_t(sample * NF * 4), uint32_t(next * sizeof(Job))};
}
constexpr JobTab make_jobs() {
  JobTab t{};
  int m = 0;
  for (int n = 0; n < 36; n++) {
    const int wg = n < 7 ? n == 4 : n & 1, j = n < 4 ? n : n < 7 ? n - 1 - 3 * wg : wg ? n / 2 - 2 : n / 2 + 2;
    if (j >= (wg ? 30 - NC_WG0 : NC_WG0)) continue;
    const int e = n < 7 ? EV_SLOT : EV_END;
    t.v[m] = make_job(n < 3 ? BAR_GDONE : n < NE ? BAR_EV + (e & 7) : BAR_PART, n < 3 ? 0 : (e >> 3) & 1, slot_of(wg, j),
                        j ? BAR_CFULL + wg * 16 + j - 1 : BAR_C0 + wg, wg * NC_WG0 + j, m + NLW);
    m++;
  }
  for (int n = 0; n < NC_EXTRA; n++) {
    const int wg = n & 1, j = n >> 1, bi = (j - 1) & 7;
    t.v[30 + n] = make_job(j == 0 ? BAR_GDONE : j <= 8 ? BAR_EV + (EV_END & 7) : BAR_CFULL + wg * 16 + 8 + bi, j <= 8 ? 0 : (((j - 1) >> 3) & 1) ^ 1,
                           j ? XOFF_SLOT + (wg * 8 + bi) * XSLOT : OFF_GIDX + wg * XSLOT, j ? BAR_CFULL + wg * 16 + bi : BAR_C0 + wg, wg * NC_EXTRA / 2 + j, 34 + n);
  }
  return t;
}
__device__ __align__(16) const JobTab g_jobs = make_jobs();
constexpr int OFF_JOB = OFF_EPI + 1040, XOFF_JOB = 24 * UNIT;
static_assert(NC_WG0 == 16 && ((EV_END >> 3) & 1) == 0, "the optional sample is the last job");

__device__ __forceinline__ int cin_start(int c) {
  return c < NGEMM ? c * NC_GEMM + min(c, NBIG) : NB - (GRID - c) * NC_EXTRA;
}
__device__ __forceinline__ int cin_count(int c) {
  return c < NGEMM ? NC_GEMM + (c < NBIG) : NC_EXTRA;
}

__device__ __forceinline__ int fold_i0(int e) { return e < 2 ? 7 * e : 2 + 6 * e; }
__device__ __forceinline__ uint32_t ldg16(const void* p) { uint16_t v; asm volatile("ld.global.nc.u16 %0, [%1];" : "=h"(v) : "l"(p)); return v; }
__device__ __forceinline__ uint32_t ldg32(const void* p) { uint32_t v; asm volatile("ld.global.nc.u32 %0, [%1];" : "=r"(v) : "l"(p)); return v; }
__device__ __forceinline__ uint4 ldg128(const void* p) {
  uint4 v; asm volatile("ld.global.nc.v4.u32 {%0,%1,%2,%3}, [%4];" : "=r"(v.x), "=r"(v.y), "=r"(v.z), "=r"(v.w) : "l"(p)); return v;
}
__device__ __forceinline__ void sts64f(uint32_t addr, float a, float b) { asm volatile("st.shared.v2.f32 [%0], {%1, %2};" ::"r"(addr), "f"(a), "f"(b) : "memory"); }
__device__ __forceinline__ float to_tf32(float v) { uint32_t r; asm("cvt.rna.tf32.f32 %0, %1;" : "=r"(r) : "f"(v)); return __uint_as_float(r); }
__device__ __forceinline__ uint4 fold_chunk(uint32_t base, const uint4 t0, const uint4 t1) {
  const uint32_t t[8] = {t0.x, t0.y, t0.z, t0.w, t1.x, t1.y, t1.z, t1.w};
  uint32_t v[4];
#pragma unroll
  for (int c = 0; c < 4; c++) {
    const float w0 = __int_as_float(lds32(base + (t[2 * c] & 0xffff))) + __int_as_float(lds32(base + (t[2 * c] >> 16)));
    const float w1 = __int_as_float(lds32(base + (t[2 * c + 1] & 0xffff))) + __int_as_float(lds32(base + (t[2 * c + 1] >> 16)));
    __nv_bfloat162 pk = __floats2bfloat162_rn(w0, w1);
    v[c] = *reinterpret_cast<uint32_t*>(&pk);
  }
  return make_uint4(v[0], v[1], v[2], v[3]);
}
__device__ __forceinline__ int cw_chunk(int u, int n) {
  return ((u < 44 ? (u >> 1) * 1792 : CW_MAIN + ((u - 44) >> 1) * 1024) + (n >> 3) * 256 + (u & 1) * 128 + (n & 7) * 16) >> 4;
}
__device__ __forceinline__ float log2_sigma(uint32_t v, int n) {
  return __reduce_add_sync(0xffffffffu, (v & 0x7fff) + ((v >> 16) & 0x7fff)) * (1.f / (128 * n)) - 126.02f;
}
__device__ __forceinline__ uint32_t acc_offset(float lg, float cap) { return __float2int_rd(fminf(fmaxf(lg + 131.5f, 0.f), cap + 127.f)) << 7 | 0x2b; }
template <typename F>
__device__ __forceinline__ void fold_weights(F keep, uint8_t* smem, uint32_t sb, int e, const __nv_bfloat16* __restrict__ wco,
                                             const __nv_bfloat16* __restrict__ ws, const __nv_bfloat16* __restrict__ table, const GPtr gp) {
  const int tid = threadIdx.x, lane = tid & 31, warp = tid >> 5;
  const uint32_t bars = sb + OFF_BAR;
  const int i0 = fold_i0(e), i = i0 + warp;
  const bool own = i < fold_i0(e + 1);
  const uint32_t wb16 = ldg16(wco + (lane < NF ? 26 + lane : 0)), wc16 = ldg16(wco + (lane < NF ? 52 + lane : 0));
  const uint32_t w116 = ldg16(wco + (own ? i : 0)), wa16 = ldg16(wco + (lane < NF ? lane : 0));
  const uint32_t sx = ldg32(table + lane * 8), s2 = ldg32(ws + 17576 + lane * 512), s3 = ldg32(ws + 2 * 17576 + lane * 512);
  const uint4* tab = gp.tab;
  const uint4 ta0 = ldg128(tab + 2 * lane), ta1 = ldg128(tab + 2 * lane + 1);
  const uint4 tb0 = ldg128(tab + 64 + 2 * (lane & 15)), tb1 = ldg128(tab + 65 + 2 * (lane & 15));
  asm volatile("barrier.cluster.arrive.relaxed.aligned;\nbarrier.cluster.wait.acquire.aligned;" ::: "memory");
  keep();
  const float lx = log2_sigma(sx, 64) + 4.7f, l1 = log2_sigma(lane < NF ? wa16 : 0, NF);
  const float l2 = log2_sigma(lane < NF ? wb16 : 0, NF), l3 = log2_sigma(lane < NF ? wc16 : 0, NF) + log2_sigma(s3, 64) + lx;
  const float ct = bf_lo(acc_offset(fmaxf(l1, fmaxf(l2, l3) + log2_sigma(s2, 64) + lx), 100.f));
  if (warp >= 6) {
    for (int t = tid - 192; t < 6 * 20; t += 64) sts64f(sb + XOFF_M + 26 * 160 + t * 8, 0.f, 0.f);
    if (warp == 6 && lane < NF) {
      sts64f(sb + XOFF_M + lane * 160 + 104, bf_lo(wb16), 0.f);
      sts64f(sb + XOFF_M + lane * 160 + 112, 0.f, 0.f);
      sts64f(sb + XOFF_M + lane * 160 + 120, 0.f, 0.f);
    }
    if (warp == 7) {
      gp.s->cw[cw_chunk(lane, 28 + e)] = make_uint4(0, 0, 0, 0);
      if (lane < 16) gp.s->cw[cw_chunk(32 + lane, 28 + e)] = make_uint4(0, 0, 0, 0);
    }
  } else {
    mbar_wait(bars + 8 * BAR_GIDX, 0);
    float m0 = 0.f, m1 = 0.f, m2 = 0.f, m3 = 0.f;
    const uint32_t a = sb + XOFF_W3 + (tid < 169 ? tid : 0) * 8;
#pragma unroll 2
    for (int g = 0; g < NF; g++) {
      const int2 v = lds64(a + g * 1352);
      const float w = __shfl_sync(0xffffffffu, bf_lo(wc16), g);
      m0 = fmaf(w, bf_lo(v.x), m0); m1 = fmaf(w, bf_hi(v.x), m1);
      m2 = fmaf(w, bf_lo(v.y), m2); m3 = fmaf(w, bf_hi(v.y), m3);
    }
    if (tid < 169) {
      const int o = tid * 2, o2 = o + 1;
      sts64f(sb + XOFF_M + (o / 13) * 160 + (o % 13) * 8, to_tf32(m0), to_tf32(m1));
      sts64f(sb + XOFF_M + (o2 / 13) * 160 + (o2 % 13) * 8, to_tf32(m2), to_tf32(m3));
    }
  }
  const uint32_t sT = sb + XOFF_S + warp * 2 * 3136, sA = sT + 3136;
  const int g = lane >> 2, c = lane & 3;
  uint32_t af[2][8];
  mbar_wait(bars + 8 * BAR_FULL, 0);
  if (own) {
#pragma unroll
    for (int k = 0; k < 8; k++) {
      const int h = 4 * k + c;
      const uint32_t a = sb + XOFF_W2 + ((h < NF ? h : 0) * 676 + i * 26 + 2 * g) * 2;
      af[0][k] = lds32(a);
      af[1][k] = lds32(a + (g < 5 ? 32 : 0));
    }
#pragma unroll 1
    for (int o = lane; o < 338; o += 32) {
      const uint32_t v = lds32(sb + XOFF_W1 + (i - (i0 & ~1)) * 1352 + o * 4);
      sts64f(sA + (o / 13) * 112 + (o % 13) * 8, bf_lo(v), bf_hi(v));
    }
    if (lane < 28) sts64f(sA + lane * 112 + 104, 0.f, 0.f);
    if (lane < 2) sts64f(sT + (26 + lane) * 112 + 104, lane == 0 ? ct : bf_lo(w116), lane == 0 ? -ct : 0.f);
  }
  bar_sync<4, 256>();
  if (own) {
#pragma unroll 1
    for (int n = 0; n < 4; n++) {
      float d[2][4] = {};
#pragma unroll
      for (int ks = 0; ks < 4; ks++) {
        const uint32_t b0 = lds32(sb + XOFF_M + (8 * ks + c) * 160 + (8 * n + g) * 4);
        const uint32_t b1 = lds32(sb + XOFF_M + (8 * ks + c + 4) * 160 + (8 * n + g) * 4);
#pragma unroll
        for (int m = 0; m < 2; m++)
          asm volatile("mma.sync.aligned.m16n8k8.row.col.f32.tf32.tf32.f32 {%0,%1,%2,%3}, {%4,%5,%6,%7}, {%8,%9}, {%0,%1,%2,%3};"
                       : "+f"(d[m][0]), "+f"(d[m][1]), "+f"(d[m][2]), "+f"(d[m][3])
                       : "r"(af[m][2 * ks] << 16), "r"(af[m][2 * ks] & 0xffff0000u), "r"(af[m][2 * ks + 1] << 16),
                         "r"(af[m][2 * ks + 1] & 0xffff0000u), "r"(b0), "r"(b1));
      }
      if (n < 3 || c < 2) {
        const uint32_t a = sT + 2 * g * 112 + (8 * n + 2 * c) * 4;
        sts64f(a, d[0][0], d[0][1]);
        sts64f(a + 112, d[0][2], d[0][3]);
        if (g < 5) {
          sts64f(a + 16 * 112, d[1][0], d[1][1]);
          sts64f(a + 17 * 112, d[1][2], d[1][3]);
        }
      }
    }
    __syncwarp();
    const int nt = i < 24 ? i : 2 * i - 24, na = i < 24 ? 32 + i : 2 * i - 23;
#pragma unroll 1
    for (int k = 0; k < 3; k++) {
      const bool isa = k == 1 || (k == 2 && lane >= 16);
      const uint4 v = fold_chunk(isa ? sA : sT, k < 2 ? ta0 : tb0, k < 2 ? ta1 : tb1);
      if (k < 2 || lane < 28 || na < 32) gp.s->cw[cw_chunk(k < 2 ? lane : 32 + (lane & 15), isa ? na : nt)] = v;
    }
  }
  __syncwarp();
  if (lane == 0) flag_add(&gp.s->foldflag);
  bar_sync<4, 256>();
  mbar_wait(bars + 8 * BAR_GDONE, 0);
  if (tid >= 128 && tid < 132) mbar_arrive(ev_bar(bars, EV_END));
}

__global__ void __cluster_dims__(2, 1, 1) __launch_bounds__(384, 1)
xdeepfm_kernel(const int* __restrict__ idx, const __nv_bfloat16* __restrict__ table, const __nv_bfloat16* __restrict__ w1,
               const __nv_bfloat16* __restrict__ b1, const __nv_bfloat16* __restrict__ w2,
               const __nv_bfloat16* __restrict__ ws, const __nv_bfloat16* __restrict__ wco,
               const __nv_bfloat16* __restrict__ bout, __nv_bfloat16* __restrict__ out, const GPtr gp,
               const __grid_constant__ CUtensorMap tmW, const __grid_constant__ CUtensorMap tmT) {
  int myidx, idx1, idx2 = 0, idx3 = 0;
  {
    const int t = threadIdx.x, b = blockIdx.x, half = (b >> 1) ^ (t >= 256 ? t >> 4 : 0);
    const int* ip = idx + (((b >> 3) & 15) * 256 + (half & 1) * 128 + (t < 256 ? min(min(t >> 5, 4) * 4 + (t >> 5) * 16 + min(t & 31, 19), 127) : (b & 1) * 64 + ((t >> 1) & 48) + (t & 15))) * NF;
    asm volatile("{\n.reg .pred p;\nsetp.ge.u32 p, %5, 256;\nld.global.nc.v2.s32 {%0, %1}, [%4];\n@p ld.global.nc.v2.s32 {%2, %3}, [%4 + 8];\n}"
                 : "=r"(myidx), "=r"(idx1), "+r"(idx2), "+r"(idx3) : "l"(ip), "r"(t));
  }
  extern __shared__ __align__(1024) uint8_t smem[];
  const uint32_t sb = (uint32_t)__cvta_generic_to_shared(smem);
  const uint32_t bars = sb + OFF_BAR;
  const int tid = threadIdx.x, lane = tid & 31;
  const int warp = __shfl_sync(0xffffffffu, tid >> 5, 0);
  const int cta = blockIdx.x;
  const bool gemm = cta < NGEMM;
  const int nt = cta & 7, rank = cta & 1;

  uint32_t sx, sw;
  uint4 bv;
  asm volatile("{\n.reg .pred p;\nsetp.eq.u32 p, %9, 7;\n@p ld.global.nc.u32 %0, [%6];\n@p ld.global.nc.u32 %1, [%7];\n@p ld.global.nc.v4.u32 {%2, %3, %4, %5}, [%8];\n}"
               : "=r"(sx), "=r"(sw), "=r"(bv.x), "=r"(bv.y), "=r"(bv.z), "=r"(bv.w)
               : "l"(table + cta * 256 + lane * 8), "l"(w1 + nt * 192 + lane * 2),
                 "l"(b1 + (lane < 24 ? nt * 192 : 1536 - 192 + (nt >> 2) * 64) + lane * 8), "r"(tid >> 5));
  auto keep = [&]() {
    asm volatile("{\n.reg .pred p;\nsetp.ne.u32 p, %0, 0;\n@p st.shared.v2.b32 [%0], {%1, %2};\n@p st.shared.v2.b32 [%0 + 8], {%3, %4};\n"
                 "@p st.shared.b32 [%0 + 16], %5;\n@p st.shared.b32 [%0 + 24], %6;\n@p st.shared.v4.b32 [%0 + 32], {%7, %8, %9, %10};\n}"
                 ::"r"((uint32_t)(size_t)table & 1), "r"(myidx), "r"(idx1), "r"(idx2), "r"(idx3), "r"(sx), "r"(sw), "r"(bv.x), "r"(bv.y), "r"(bv.z), "r"(bv.w) : "memory");
  };
  if (warp == 8 && elect1()) {
    mbar_init(bars + 8 * BAR_GIDX, 1);
    mbar_init(bars + 8 * BAR_FULL, 1);
    mbar_init(bars + 8 * BAR_W0, 1);
    asm volatile("fence.mbarrier_init.release.cluster;" ::: "memory");
    if (gemm) {
      mbar_expect_tx(bars + 8 * BAR_W0, 4 * UNIT);
#pragma unroll
      for (int i = 0; i < 4; i++)
        tma_load(sb + (U_W + i) * UNIT, &tmW, i < 3 ? nt * 192 + i * 64 : 1536 + (nt >> 2) * 64, 0, bars + 8 * BAR_W0);
    } else {
      mbar_expect_tx(bars + 8 * BAR_GIDX, 35152);
      bulk_load(sb + XOFF_W3, ws + 2 * 17576, 35152, bars + 8 * BAR_GIDX);
    }
  }
  if (threadIdx.x < 256) {}
  else if (threadIdx.x >= 384 - 16) {
    const int l = threadIdx.x & 7;
    if (l < 7) asm volatile("prefetch.global.L2 [%0];" ::"l"(w1 + (((cta >> 3 & 15) * 2 + (cta & 1)) * 2 + ((threadIdx.x >> 3) & 1)) * DIN + (l < 6 ? (cta & 6) * 192 + l * 64 : 1536 + (cta & 4) * 16)));
  }
  else if (threadIdx.x >= 352 && threadIdx.x < 359) {
    const int l = blockIdx.x * 7 + threadIdx.x - 352;
    if (l < 824) asm volatile("prefetch.global.L2 [%0];" ::"l"(ws + (823 - l) * 64));
  }

  const int c0 = cin_start(cta), ncin = cin_count(cta);

  if (warp >= 8) {
    const int pw = warp - 8;
    const uint32_t cidx = sb + (gemm ? OFF_CIDX : XOFF_CIDX);
    const bool lead = elect1();
    if (lead) {
      if (pw) mbar_init(bars + 8 * (pw < 3 ? BAR_FULL + pw : BAR_CIDX), 1);
      else mbar_init(bars + 8 * BAR_GDONE, 4);
      asm volatile("fence.mbarrier_init.release.cluster;" ::: "memory");
    }
    __syncwarp();
    asm volatile("barrier.cluster.arrive.relaxed.aligned;" ::: "memory");
    if (lead) {
      if (gemm) w_prefetch(w1, 1, cta, pw);
      if (pw == 0) {
        if (gemm) {
          mbar_expect_tx(bars + 8 * BAR_FULL, 2 * UNIT);
          asm volatile("prefetch.tensormap [%0];" ::"l"(&tmT) : "memory");
        } else {
          const int i0 = fold_i0(cta - NGEMM) & ~1, ni = NF - i0 < 8 ? NF - i0 : 8;
          mbar_expect_tx(bars + 8 * BAR_FULL, 35152 + ni * 1352);
          bulk_load(sb + XOFF_W1, ws + i0 * 676, ni * 1352, bars + 8 * BAR_FULL);
          bulk_load(sb + XOFF_W2, ws + 17576, 35152, bars + 8 * BAR_FULL);
        }
      } else if (pw == 3 && !gemm) {
        const int a0 = c0 & ~1, a1 = (c0 + ncin + 1) & ~1;
        mbar_expect_tx(bars + 8 * BAR_CIDX, (a1 - a0) * NF * 4 + sizeof(JobTab));
        bulk_load(cidx, idx + a0 * NF, (a1 - a0) * NF * 4, bars + 8 * BAR_CIDX);
        bulk_load(sb + XOFF_JOB, gp.jobs, sizeof(JobTab), bars + 8 * BAR_CIDX);
      }
    }
    __syncwarp();
    asm volatile("setmaxnreg.dec.sync.aligned.u32 24;");
    if (elect1()) {
      mbar_init(bars + 8 * (BAR_EV + pw), 4);
      mbar_init(bars + 8 * (BAR_EV + 4 + pw), 4);
      mbar_init(bars + 8 * (BAR_FULL + 4 + pw), 1);
      mbar_init(bars + 8 * (pw == 2 ? BAR_CW : BAR_DNN + pw), pw == 2 ? 1 : 1 << pw);
      if (pw == 0) mbar_init(bars + 8 * (BAR_FULL + 3), 1);
#pragma unroll
      for (int i = 0; i < 8; i++)
        mbar_init(bars + 8 * (BAR_CFULL + pw * 8 + i), (!gemm && (pw & 1)) ? 4 : 1);
      if (pw < 2) mbar_init(bars + 8 * (BAR_C0 + pw), 1);
      asm volatile("fence.mbarrier_init.release.cluster;" ::: "memory");
    }
    __syncwarp();
    bar_sync<6, 128>();
    asm volatile("barrier.cluster.wait.acquire.aligned;" ::: "memory");
    if (!gemm && elect1()) mbar_arrive(bars + 8 * BAR_GDONE);
    __syncwarp();
    if (gemm) {
      {
        const uint32_t a = sb + OFF_GIDX + ((lane >> 4) * 64 + pw * 16 + (lane & 15)) * NF * 4;
        asm volatile("st.shared.v2.b32 [%0], {%1, %2};\nst.shared.v2.b32 [%0 + 8], {%3, %4};"
                     ::"r"(a), "r"(myidx), "r"(idx1), "r"(idx2), "r"(idx3) : "memory");
        keep();
        __syncwarp();
      }
      if (elect1()) {
#pragma unroll
        for (int j = 0; j < 16; j += 8) {
          int r[8];
#pragma unroll
          for (int i = 0; i < 8; i++) r[i] = lds32(sb + OFF_GIDX + ((64 + pw * 16 + j + i) * NF) * 4);
#pragma unroll
          for (int i = 0; i < 8; i++) tma_row_mc(sb + U_XB * UNIT + (rank * 64 + pw * 16 + j + i) * 128, &tmT, r[i], bars + 8 * BAR_FULL);
        }
        int s = 1;
#pragma unroll 1
        for (int fi = 1; fi < NF; fi++) {
          const int f = fresh(fi), pw = fresh(warp) - 8, ct = fresh(cta), nt = ct & 7;
          const int t = f - FS, st = t < 0 ? s : (t & 3) ^ ((t >> 1) & 1), e = f - 3 - (t > 1);
          const uint32_t fb = bars + 8 * (BAR_FULL + (f & 7)), ia = sb + OFF_GIDX + (pw * 16 * NF + f) * 4;
          const uint32_t d = sb + (st == 3 ? U_SP : 2 * st) * UNIT + ((ct & 1) * 64 + pw * 16) * 128;
          if (f == 4) mbar_wait(bars + 8 * BAR_GIDX, 0);
          int r[2][RB];
#pragma unroll
          for (int i = 0; i < RB; i++) r[0][i] = lds32(ia + i * NF * 4);
          if (e >= 0) mbar_wait(ev_bar(bars, e), ev_par(e));
          if (pw == 0) mbar_expect_tx(fb, t < 0 ? 8 * UNIT : 6 * UNIT);
#pragma unroll
          for (int j = 0; j < 16 / RB; j++) {
#pragma unroll
            for (int i = 0; i < RB; i++) r[(j + 1) & 1][i] = lds32(ia + (RB * j + RB + i + (RB * j + RB >= 16) * 48) * NF * 4);
#pragma unroll
            for (int i = 0; i < RB; i++) tma_row_mc(d + (RB * j + i) * 128, &tmT, r[j & 1][i], fb);
          }
          if (t < 0) {
#pragma unroll
            for (int j = 0; j < 16 / RB; j++) {
              if (j + 1 < 16 / RB) {
#pragma unroll
                for (int i = 0; i < RB; i++) r[(j + 1) & 1][i] = lds32(ia + (64 + RB * j + RB + i) * NF * 4);
              }
#pragma unroll
              for (int i = 0; i < RB; i++) tma_row_mc(d + U_XB * UNIT + (RB * j + i) * 128, &tmT, r[j & 1][i], fb);
            }
          }
          tma_load(sb + (U_W + 4 * st + pw) * UNIT, &tmW, pw < 3 ? nt * 192 + pw * 64 : 1536 + (nt >> 2) * 64, f * 64, fb);
          if (f == GI && pw < 2) {
            if (pw == 0) mbar_expect_tx(bars + 8 * BAR_GIDX, 128 * NF * 4);
            bulk_load(sb + OFF_GIDX + pw * 64 * NF * 4, idx + ((ct >> 3) * 256 + (((ct >> 1) ^ pw) & 1) * 128 + (ct & 1) * 64) * NF, 64 * NF * 4, bars + 8 * BAR_GIDX);
          }
          if (f == GI && pw == 2) {
            const int c0 = cin_start(ct), a0 = c0 & ~1, n = (((c0 + cin_count(ct) + 1) & ~1) - a0) * NF * 4;
            mbar_expect_tx(bars + 8 * BAR_CIDX, n + 30 * sizeof(Job));
            bulk_load(sb + OFF_CIDX, idx + a0 * NF, n, bars + 8 * BAR_CIDX);
            bulk_load(sb + OFF_JOB, gp.jobs, 30 * sizeof(Job), bars + 8 * BAR_CIDX);
          }
          if (f + WD < NF) w_prefetch(w1, f + WD, ct, pw);
          if (++s == 3) s = 0;
        }
        mbar_wait(bars + 8 * BAR_T, 0);
#pragma unroll 1
        for (int ti = 0; ti < 8; ti++) {
          const int t = fresh(ti), pw = fresh(warp) - 8, e = t < 4 ? 22 - !t : 19 + t;
          const uint32_t ia = sb + OFF_TIDX + t * 256 + pw * 64, fb = bars + 8 * (BAR_FULL + ((NF + t) & 7));
          const uint32_t d = sb + b_x(t) * UNIT + ((fresh(cta) & 1) * 64 + pw * 16) * 128;
          int4 r[2];
          r[0] = lds128(ia);
          r[1] = lds128(ia + 16);
          mbar_wait(ev_bar(bars, e), ev_par(e));
          if (pw == 0) mbar_expect_tx(fb, t < 3 ? 2 * UNIT : 5 * UNIT);
#pragma unroll
          for (int j = 0; j < 4; j++) {
            tma_row_mc(d + (4 * j + 0) * 128, &tmT, r[j & 1].x, fb);
            tma_row_mc(d + (4 * j + 1) * 128, &tmT, r[j & 1].y, fb);
            tma_row_mc(d + (4 * j + 2) * 128, &tmT, r[j & 1].z, fb);
            tma_row_mc(d + (4 * j + 3) * 128, &tmT, r[j & 1].w, fb);
            if (j < 2) r[j & 1] = lds128(ia + 32 + 16 * j);
          }
        }
        mbar_arrive(bars + 8 * BAR_GDONE);
      }
      __syncwarp();
    }
    {
    int cta; asm volatile("mov.u32 %0, %%ctaid.x;" : "=r"(cta));
    cta = __shfl_sync(0xffffffffu, cta, 0);
    const bool gemm = cta < NGEMM;
    const int bt = cta >> 3, nt = cta & 7;
    const int c0 = cin_start(cta), ncin = cin_count(cta);
    if (pw == 3) {
      if (elect1()) {
        if (!gemm) flag_wait(&gp.s->foldflag, (gp.s->epoch[fresh(cta)] + 1) * NEXTRA * 8, 0);
        asm volatile("fence.proxy.async.global;" ::: "memory");
        if (gemm) mbar_wait(ev_bar(bars, EV_CW), ev_par(EV_CW));
        mbar_expect_tx(bars + 8 * BAR_CW, CW_BYTES);
        bulk_load(sb + OFF_CW, gp.s->cw, CW_CUT * 1792, bars + 8 * BAR_CW);
        bulk_load(sb + OFF_CW2, gp.s->cw + CW_CUT * 1792 / 16, (22 - CW_CUT) * 1792, bars + 8 * BAR_CW);
        bulk_load(sb + OFF_CWL, gp.s->cw + CW_MAIN / 16, CW_LIN, bars + 8 * BAR_CW);
      }
      __syncwarp();
    }
    if (pw < NLW || !gemm) {
      if (elect1()) {
        const int ct = blockIdx.x, end = cin_count(ct);
        const bool gemm = ct < NGEMM;
        const uint32_t cidx = sb + (gemm ? OFF_CIDX : XOFF_CIDX) + (cin_start(ct) & 1) * NF * 4;
        mbar_wait(bars + 8 * BAR_GDONE, 0);
        mbar_wait(bars + 8 * BAR_CIDX, 0);
        const uint32_t last = ((gemm ? 0 : 30) + end) * sizeof(Job), jobs = sb + (gemm ? OFF_JOB : XOFF_JOB);
#pragma unroll 1
        for (uint32_t o = ((gemm ? -8 : 22) + warp) * sizeof(Job); o < last;) {
          const int2 j0 = lds64(jobs + o), j1 = lds64(jobs + o + 8), j2 = lds64(jobs + o + 16);
          const Job job = {uint32_t(j0.x), uint32_t(j0.y), uint32_t(j1.x), uint32_t(j1.y), uint32_t(j2.x), uint32_t(j2.y)};
          const uint32_t d = sb + job.slot, cb = sb + job.full, ia = cidx + job.idx;
          o = job.next;
          mbar_wait(sb + job.wait, job.par);
          mbar_expect_tx(cb, NF * 128);
#pragma unroll
          for (int k = 0; k < NF; k += 2 * LB) {
            int2 r[LB];
#pragma unroll
            for (int i = 0; i < LB; i++) if (k + 2 * i < NF) r[i] = lds64(ia + (k + 2 * i) * 4);
#pragma unroll
            for (int i = 0; i < LB; i++) if (k + 2 * i < NF) {
              tma_row(d + (k + 2 * i) * 128, &tmT, r[i].x, cb);
              tma_row(d + (k + 2 * i + 1) * 128, &tmT, r[i].y, cb);
            }
          }
        }
      }
      __syncwarp();
    }
    if (pw == 3) {
      unsigned epoch;
      asm volatile("ld.global.u32 %0, [%1];" : "=r"(epoch) : "l"(gp.s->epoch + fresh(cta)));
      epoch++;
      const float bo = (sb & 0xFFFFFF) == SMEM_BASE ? bf2f(bout[0]) : __int_as_float(0x7fc00000);
      if (gemm) {
        mbar_wait(bars + 8 * BAR_PART, 0);
        float4* dst = reinterpret_cast<float4*>(gp.s->part + nt * NB + bt * 256);
        dst[lane] = lds128f(sb + OFF_PART + lane * 16);
        dst[lane + 32] = lds128f(sb + OFF_PART + 512 + lane * 16);
        __syncwarp();
        if (lane == 0) flag_add(gp.s->dflag + (fresh(cta) >> 3) * 8);
      }
      flag_wait(gp.s->dflag + ((lane == 0 ? c0 : c0 + ncin - 1) >> 8) * 8, epoch * 8, 200);
      __syncwarp();
#pragma unroll 1
      for (int r = lane; r < ncin; r += 32) {
        float s = bo;
#pragma unroll
        for (int n = 0; n < 8; n++) s += __ldcg(gp.s->part + n * NB + c0 + r);
        sts32f(sb + OFF_DNN + r * 4, s);
      }
      __syncwarp();
      if (lane == 0) { mbar_arrive(bars + 8 * BAR_DNN); gp.s->epoch[fresh(cta)] = epoch; }
    }
    }
  } else {
    const int wg = warp >> 2;
    const int p = tid & 127;
    if (gemm) {
      asm volatile("barrier.cluster.arrive.relaxed.aligned;" ::: "memory");
      if (warp == 7) {
        asm volatile("st.shared.b32 [%0], %1;" ::"r"(sb + OFF_INIT + 4608 + lane * 4), "r"(0x3f003f00) : "memory");
        const int lg = __reduce_add_sync(0xffffffffu, (sx & 0x7fff) + ((sx >> 16) & 0x7fff) + (sw & 0x7fff) + ((sw >> 16) & 0x7fff));
        const uint32_t co = (min(max((lg >> 6) - int((127 - 11.8 - OB) * 128), 0), (130 + OB) * 128) & 0x7f80) | 0x2b;
        const uint32_t bw[4] = {bv.x, bv.y, bv.z, bv.w};
#pragma unroll
        for (int i = 0; i < 8; i++)
          asm volatile("st.shared.v4.b32 [%0], {%1, %2, %2, %2};" ::"r"(sb + OFF_INIT + lane * 144 + i * 16), "r"(__byte_perm(bw[i >> 1], co, i & 1 ? 0x5432 : 0x5410)), "r"(0) : "memory");
        sts32f(sb + OFF_EPI + 1024, -ALPHA * __uint_as_float((co << 16) - 39));
        asm volatile("fence.proxy.async.shared::cta;" ::: "memory");
        bar_arrive<5, 160>();
      } else {
        const int row = min(warp, 4) * 4 + warp * 16 + (lane >> 3);
        const uint32_t a = sb + row * 128 + (((lane ^ row) & 7) << 4);
        const __nv_bfloat16* src = table + (lane & 7) * 8;
        const int l0 = ((fresh(a) >> 7) & 3) | (fresh((int)(size_t)src) & 1);
#pragma unroll
        for (int i = 0; i < 5; i++)
          asm volatile("{\n.reg .pred p;\n.reg .b32 r;\n.reg .b64 a;\nsetp.ne.b32 p, %4, 0;\nshfl.sync.idx.b32 r, %2, %3, 31, 0xffffffff;\n"
                       "mad.wide.s32 a, r, 128, %1;\n@p cp.async.cg.shared.global [%0], [a], 16;\n}"
                       ::"r"((a ^ (i & 1) * 64) + i * 512), "l"(src), "r"(myidx), "r"(4 * i + l0), "r"(int(i < 4 || warp < 4)) : "memory");
      }
      keep();
      asm volatile("barrier.cluster.wait.acquire.aligned;" ::: "memory");
    } else {
      fold_weights(keep, smem, sb, cta - NGEMM, wco, ws, table, gp);
    }
    asm volatile("setmaxnreg.inc.sync.aligned.u32 224;");
    float r0 = 0.f, r1 = 0.f, r2 = 0.f, r3 = 0.f;
    float d1[96];
    Gelu<24> g1;
    const uint32_t ep = sb + OFF_EPI + (lane & 3) * 16;
    auto load_w = [&](int t) {
      const int w = warp & 3;
      if (w < 3 && elect1())
        tma_load(sb + (b_w(t) + b_ws(t) * w) * UNIT, &tmW, nt * 192 + w * 64, (NF - 1 - t) * 64, bars + 8 * (BAR_FULL + ((NF + t) & 7)));
    };
    int role; asm volatile("mov.u32 %0, %%ctaid.x;" : "=r"(role));
    role = role < NGEMM ? wg : 2;
    if (fresh(role) == 0) {
      asm volatile("setmaxnreg.inc.sync.aligned.u32 256;");
      float d0[96], dx[32], dw[96];
      Gelu<24> g0;
      bar_sync<5, 160>();
      wg_fence();
      wgmma_ss_n256<0>(dw, dx, ONES_DESC, INIT_DESC, 0);
      wgmma_ss_n192<0>(d0, ONES_DESC, INIT_DESC, 0);
      wg_commit();
      mbar_wait(bars + 8 * BAR_W0, 0);
      asm volatile("cp.async.wait_all;" ::: "memory");
      asm volatile("fence.proxy.async.shared::cta;" ::: "memory");
      bar_sync<2, 256>();
      const uint64_t dA0 = desc_x(rank), dA1 = desc_x(rank ^ 1);
      wg_fence();
#pragma unroll
      for (int k = 0; k < 4; k++) {
        wgmma_ss_n256(dw, dx, dA0 + 2 * k, desc_w(U_W) + 128 * k, 1);
        wgmma_ss_n192(d0, dA1 + 2 * k, desc_w(U_W) + 128 * k, 1);
      }
      wg_commit();
      constexpr unsigned long long STAGES = 0xb4b4924924924ull;
#pragma unroll 1
      for (int f = 1; f < NF - 3; f++) {
        mbar_wait(bars + 8 * (BAR_FULL + (f & 7)), (f >> 3) & 1);
        const int st = (STAGES >> (2 * f)) & 3, xo = (st == 3 ? U_SP : 2 * st) * (UNIT / 16);
        const uint64_t dB = desc_w(U_W + 4 * st);
        wg_fence();
        wgmma_ss_n256(dw, dx, dA0 + xo, dB, 1);
        wgmma_ss_n192(d0, dA1 + xo, dB, 1);
        wg_commit();
        wg_wait<1>();
        if (p < (f > FS ? 4 : 2)) mbar_arrive_cta(ev_bar(bars, f - 1), p & 1);
#pragma unroll
        for (int k = 1; k < 4; k++) {
          wgmma_ss_n256(dw, dx, dA0 + xo + 2 * k, dB + 128 * k, 1);
          wgmma_ss_n192(d0, dA1 + xo + 2 * k, dB + 128 * k, 1);
        }
        wg_commit();
      }
      {
        constexpr int x3 = 2 * (UNIT / 16), x4 = U_SP * (UNIT / 16), x5 = 4 * (UNIT / 16);
        const uint64_t dB3 = desc_w(U_W + 4), dB4 = desc_w(U_W + 12), dB5 = desc_w(U_W + 8);
        mbar_wait(bars + 8 * (BAR_FULL + 7), 0);
        tile_step(d0, dA1 + x3, dB3);
        wg_wait<1>();
        if (p < 4) mbar_arrive_cta(ev_bar(bars, NF - 4), p & 1);
        mbar_wait(bars + 8 * (BAR_FULL + 0), 1);
        tile_step(d0, dA1 + x4, dB4);
        if (WK) wide_step<0, WK>(dw, dx, dA0 + x3, dB3);
        mbar_wait(bars + 8 * (BAR_FULL + 1), 1);
        tile_step(d0, dA1 + x5, dB5);
        wide_step<WK, 4>(dw, dx, dA0 + x3, dB3);
        mbar_wait(bars + 8 * BAR_T, 0);
        g0.start(ep, sb);
        wg_wait<1>();
        wide_step(dw, dx, dA0 + x4, dB4);
        g0.part<0, PE1>(d0, r0, r1);
        wg_wait<1>();
        if (p < 4) mbar_arrive_cta(ev_bar(bars, NF - 3), p & 1);
        wide_step<0, HK>(dw, dx, dA0 + x5, dB5);
        g0.part<PE1, PE2>(d0, r0, r1);
        wg_wait<1>();
        bar_arrive<4, 256>();
        if (p < 4) mbar_arrive_cta(ev_bar(bars, NF - 2), p & 1);
        wide_step<HK, 4>(dw, dx, dA0 + x5, dB5);
        g0.part<PE2, PE0>(d0, r0, r1);
        wg_wait<0>();
        load_w(3);
        if (p < 4) mbar_arrive_cta(ev_bar(bars, NF - 1), p & 1);
      }
      g0.part<PE0, g0.END>(d0, r0, r1);
      Gelu<8> gx;
      gx.start(ep + 12 * 64, sb);
      gx.part<0, gx.END>(dx, r2, r3);
      hand_on(d1, dw);
      g1.take(g0);
      asm volatile("setmaxnreg.dec.sync.aligned.u32 224;");
    }
    if (fresh(role) == 1) {
      float d0[96], dw[96];
      bar_sync<3, 128>();
      wg_fence();
      wgmma_ss_n192<0>(d0, ONES_DESC, INIT_DESC, 0);
      wgmma_ss_n192<0>(dw, ONES_DESC + ((size_t)table & 1), INIT_DESC, 0);
      wg_commit();
      asm volatile("cp.async.wait_all;" ::: "memory");
      asm volatile("fence.proxy.async.shared::cta;" ::: "memory");
      bar_arrive<2, 256>();
      mbar_wait(bars + 8 * BAR_W0, 0);
      mbar_wait(bars + 8 * BAR_FULL, 0);
      wg_fence();
#pragma unroll
      for (int k = 0; k < 4; k++) {
        wgmma_ss_n192(d0, desc_x(U_XB) + 2 * k, desc_w(U_W) + 128 * k, 1);
        wgmma_ss_n192(dw, desc_x(U_XB + 1) + 2 * k, desc_w(U_W) + 128 * k, 1);
      }
      wg_commit();
      int s = 1;
#pragma unroll 1
      for (int f = 1; f < FS; f++) {
        mbar_wait(bars + 8 * (BAR_FULL + (f & 7)), (f >> 3) & 1);
        const uint64_t dA = desc_x(U_XB + 2 * s), dB = desc_w(U_W + 4 * s);
        wg_fence();
        wgmma_ss_n192(d0, dA, dB, 1);
        wgmma_ss_n192(dw, dA + 512, dB, 1);
        wg_commit();
        wg_wait<1>();
        if (p < 2) mbar_arrive_cta(ev_bar(bars, f - 1), p);
#pragma unroll
        for (int k = 1; k < 4; k++) {
          wgmma_ss_n192(d0, dA + 2 * k, dB + 128 * k, 1);
          wgmma_ss_n192(dw, dA + 512 + 2 * k, dB + 128 * k, 1);
        }
        wg_commit();
        if (++s == 3) s = 0;
      }
      wg_wait<0>();
      if (p < 2) mbar_arrive_cta(ev_bar(bars, FS - 1), p);
      {
        const uint32_t a = sb + OFF_GIDX + 64 * NF * 4;
        const uint32_t ww = ldg32(w2 + 2 * p + (p < 96 ? nt * 192 : 1536 - 192 + (nt >> 2) * 64));
        int v[4];
#pragma unroll
        for (int i = 0; i < 4; i++) v[i] = lds32(a + (((p & 15) * 4 + i) * NF + (NF - 1 - (p >> 4))) * 4);
        bar_sync<3, 128>();
        asm volatile("st.shared.v4.b32 [%0], {%1, %2, %3, %4};" ::"r"(sb + OFF_TIDX + p * 16), "r"(v[0]), "r"(v[1]), "r"(v[2]), "r"(v[3]) : "memory");
        sts64f(sb + OFF_EPI + (p >> 3) * 64 + (p & 3) * 16 + (p & 4) * 2, (0.5f / ALPHA) * bf_lo(ww), (0.5f / ALPHA) * bf_hi(ww));
        bar_sync<3, 128>();
        if (p < 2) {
          flag_wait(&gp.s->foldflag, (gp.s->epoch[cta] + 1) * NEXTRA * 8, 0);
          mbar_arrive(bars + 8 * BAR_T);
        }
        __syncwarp();
      }
      mbar_wait(ev_bar(bars, FS), ev_par(FS));
      mbar_wait(bars + 8 * (BAR_FULL + 2), 1);
      bar_sync<4, 256>();
#pragma unroll
      for (int t = 0; t < 4; t++) {
        if (t) mbar_wait(bars + 8 * (BAR_FULL + 2 + t), 1);
        const uint64_t dA = desc_x(b_x(t)), dB = desc_w(b_w(t), b_ws(t));
        wg_fence();
#pragma unroll
        for (int k = 0; k < 4; k++) {
          wgmma_ss_n192(d0, dA + 2 * k, dB + 128 * k, 1);
          wgmma_ss_n192(dw, dA + 512 + 2 * k, dB + 128 * k, 1);
          if (k == 1 && t) {
            wg_commit();
            wg_wait<1>();
            mbar_wait(ev_bar(bars, NF - 1), ev_par(NF - 1));
            load_w(3 + t);
            if (t == 1 && p < 4) mbar_arrive_cta(ev_bar(bars, 26), p & 1);
            wg_fence();
          }
        }
        wg_commit();
      }
      mbar_wait(bars + 8 * (BAR_FULL + 6), 1);
      tile_step(d0, desc_x(b_x(4)), desc_w(b_w(4)));
      wg_wait<1>();
      load_w(7);
      if (p < 4) mbar_arrive(ev_bar(bars, EV_CW));
      mbar_wait(bars + 8 * (BAR_FULL + 7), 1);
      tile_step(d0, desc_x(b_x(5)), desc_w(b_w(5)));
      mbar_wait(bars + 8 * (BAR_FULL + 0), 0);
      tile_step(d0, desc_x(b_x(6)), desc_w(b_w(6)));
      mbar_wait(bars + 8 * (BAR_FULL + 1), 0);
      tile_step(d0, desc_x(b_x(7)), desc_w(b_w(7), 4));
      tile_step(dw, desc_x(b_x(4) + 1), desc_w(b_w(4)));
      Gelu<24> g0;
      g0.start(ep, sb);
      wg_wait<1>();
      tile_step(dw, desc_x(b_x(5) + 1), desc_w(b_w(5)));
      g0.part<0, PS>(d0, r0, r1);
      wg_wait<1>();
      if (p < 4) mbar_arrive(ev_bar(bars, 30));
      tile_step(dw, desc_x(b_x(6) + 1), desc_w(b_w(6)));
      g0.part<PS, 2 * PS>(d0, r0, r1);
      wg_wait<1>();
      if (p < 4) mbar_arrive(ev_bar(bars, 31));
      tile_step(dw, desc_x(b_x(7) + 1), desc_w(b_w(7), 4));
      g0.part<2 * PS, 2 * PS + PS2>(d0, r0, r1);
      wg_wait<0>();
      if (p < 4) mbar_arrive(ev_bar(bars, EV_END));
      g0.part<2 * PS + PS2, g0.END>(d0, r0, r1);
      hand_on(d1, dw);
      g1.take(g0);
    }
    g1.ep = ep;
    if (fresh(role) < 2) g1.part<0, g1.END - GK, false>(d1, r2, r3);

    {
    int cta, tid;
    asm volatile("mov.u32 %0, %%ctaid.x;" : "=r"(cta));
    asm volatile("mov.u32 %0, %%tid.x;" : "=r"(tid));
    const bool gemm = role < 2;
    const int lane = tid & 31, p = tid & 127;
    const int rb = !wg ? 0 : gemm ? NC_WG0 : NC_EXTRA / 2;
    const int nj = !gemm ? NC_EXTRA / 2 : wg ? cin_count(cta) - NC_WG0 : NC_WG0;
    const uint32_t cinb = sb + (gemm ? OFF_CIN + rb * CROW : wg ? XOFF_CIN1 : XOFF_CIN0);
    CinCtx c;
    cin_setup(c, sb, wg, tid, gemm, nj);
    c.co = cinb;
    c.cin = p * 4;
    uint32_t ra, on;
    float dn;
    __nv_bfloat16* op;
    auto prepare = [&](int r) {
      on = (p & 7) == 0 && r >= 0;
      r = max(r, 0);
      ra = cinb + (p & 7) * 16 + r * CROW;
      dn = __int_as_float(lds32(sb + OFF_DNN + (rb + r) * 4));
      op = out + cin_start(cta) + rb + r;
      dn *= 0.125f;
      asm volatile("" : "+r"(ra), "+r"(on), "+f"(dn), "+l"(op));
      sched_fence();
    };
    auto result = [&]() {
      const float4 v0 = lds128f(ra), v1 = lds128f(ra + 128), v2 = lds128f(ra + 256), v3 = lds128f(ra + 384);
      float s = ((((v0.x + dn) + v0.y) + (v0.z + v0.w)) + ((v1.x + v1.y) + (v1.z + v1.w))) +
                (((v2.x + v2.y) + (v2.z + v2.w)) + ((v3.x + v3.y) + (v3.z + v3.w)));
      s += __shfl_xor_sync(0xffffffffu, s, 1);
      s += __shfl_xor_sync(0xffffffffu, s, 2);
      s += __shfl_xor_sync(0xffffffffu, s, 4);
      asm volatile("{\n.reg .pred p;\n.reg .b16 v;\nsetp.ne.u32 p, %2, 0;\ncvt.rn.bf16.f32 v, %1;\n@p st.global.b16 [%0], v;\n}" ::"l"(op), "f"(s), "r"(on) : "memory");
    };
    cin_run(c, [&](uint32_t (&x)[11][2]) {
      mbar_wait(bars + 8 * BAR_GDONE, 0);
      mbar_wait(bars + 8 * (BAR_C0 + wg), 0);
      const uint32_t first = sb + (!gemm ? OFF_GIDX + wg * XSLOT : wg ? 24 * UNIT : OFF_GIDX + 2 * XSLOT);
      g1.part<g1.END - GK, g1.END, false>(d1, r2, r3, [&](int i) { cin_ldsm(c, first, x, i); });
#pragma unroll
      for (int i = GK; i < 5; i++) cin_ldsm(c, first, x, i);
      mbar_wait(bars + 8 * BAR_CW, 0);
    }, [&]() {
      sched_fence();
      const bool b0 = lane & 1, b1_ = lane & 2;
      float a = b0 ? r1 : r0, b = b0 ? r0 : r1, cc = b0 ? r3 : r2, d = b0 ? r2 : r3;
      a += __shfl_xor_sync(0xffffffffu, b, 1);
      cc += __shfl_xor_sync(0xffffffffu, d, 1);
      float e = b1_ ? cc : a, f = b1_ ? a : cc;
      e += __shfl_xor_sync(0xffffffffu, f, 2);
      const uint32_t row4 = (tid & 0x1c) | ((tid & 1) << 5) | ((tid & 0x60) << 1) | ((tid & 2) << 7);
      sts32f(sb + OFF_PART + (row4 ^ (((((cta >> 1) ^ wg) & 1) << 9) | ((~cta & ~wg & 1) << 8))), e);
      __syncwarp();
      if (lane == 0) mbar_arrive(bars + 8 * BAR_PART);
      mbar_wait(ev_bar(bars, gemm ? EV_CIN : EV_END), gemm);
    }, [&]() {
      mbar_wait(bars + 8 * BAR_DNN, 0);
      prepare(nj - 16 + (p >> 3));
    });
    asm volatile("bar.sync %0, 128;" ::"r"(1 + 2 * wg) : "memory");
    result();
#pragma unroll 1
    for (int r = nj - 32; r > -16; r -= 16) {
      prepare(r + (p >> 3));
      result();
    }
    }
  }
}

typedef CUresult (*EncodeFn)(CUtensorMap*, CUtensorMapDataType, cuuint32_t, void*, const cuuint64_t*, const cuuint64_t*,
                             const cuuint32_t*, const cuuint32_t*, CUtensorMapInterleave, CUtensorMapSwizzle,
                             CUtensorMapL2promotion, CUtensorMapFloatOOBfill);

extern "C" void kernel_launch(void* const* d_in, const int* in_sizes, int n_in, void* d_out, int out_size) {
  void* fn = nullptr;
  cudaDriverEntryPointQueryResult q;
  cudaGetDriverEntryPoint("cuTensorMapEncodeTiled", &fn, cudaEnableDefault, &q);
  EncodeFn enc = (EncodeFn)fn;
  CUtensorMap tmW, tmT;
  const cuuint32_t es[3] = {1, 1, 1};
  {
    cuuint64_t dims[2] = {DIN, DIN}, st[1] = {DIN * 2};
    cuuint32_t box[2] = {64, 64};
    enc(&tmW, CU_TENSOR_MAP_DATA_TYPE_BFLOAT16, 2, d_in[4], dims, st, box, es, CU_TENSOR_MAP_INTERLEAVE_NONE,
        CU_TENSOR_MAP_SWIZZLE_128B, CU_TENSOR_MAP_L2_PROMOTION_NONE, CU_TENSOR_MAP_FLOAT_OOB_FILL_NONE);
  }
  {
    cuuint64_t dims[2] = {64, (cuuint64_t)(in_sizes[1] / 64)}, st[1] = {128};
    cuuint32_t box[2] = {64, 1};
    enc(&tmT, CU_TENSOR_MAP_DATA_TYPE_BFLOAT16, 2, d_in[1], dims, st, box, es, CU_TENSOR_MAP_INTERLEAVE_NONE,
        CU_TENSOR_MAP_SWIZZLE_128B, CU_TENSOR_MAP_L2_PROMOTION_NONE, CU_TENSOR_MAP_FLOAT_OOB_FILL_NONE);
  }
  GPtr gp;
  gp.zero = 0;
  cudaGetSymbolAddress((void**)&gp.s, g_scratch);
  cudaGetSymbolAddress((void**)&gp.tab, g_slot_tab);
  cudaGetSymbolAddress((void**)&gp.jobs, g_jobs);
  cudaFuncSetAttribute(xdeepfm_kernel, cudaFuncAttributeMaxDynamicSharedMemorySize, SMEM_BYTES);
  xdeepfm_kernel<<<GRID, 384, SMEM_BYTES, cudaStreamPerThread>>>(
      (const int*)d_in[0], (const __nv_bfloat16*)d_in[1], (const __nv_bfloat16*)d_in[4], (const __nv_bfloat16*)d_in[5],
      (const __nv_bfloat16*)d_in[6], (const __nv_bfloat16*)d_in[2], (const __nv_bfloat16*)d_in[3],
      (const __nv_bfloat16*)d_in[7], (__nv_bfloat16*)d_out, gp, tmW, tmT);
}
```

```cpp
#include <cuda_runtime.h>
#include <cuda_bf16.h>
#include <cuda.h>
#include <stdint.h>

template <int TB = 1>
__device__ __forceinline__ void wgmma_ss_n256(float (&d)[96], float (&e)[32], uint64_t descA, uint64_t descB, int scaleD) {
  asm volatile("{\n.reg .pred p;\nsetp.ne.b32 p, %130, 0;\n"
      "wgmma.mma_async.sync.aligned.m64n256k16.f32.bf16.bf16 {"
      "%0, %1, %2, %3, %4, %5, %6, %7, %8, %9, %10, %11, %12, %13, %14, %15,"
      "%16, %17, %18, %19, %20, %21, %22, %23, %24, %25, %26, %27, %28, %29, %30, %31,"
      "%32, %33, %34, %35, %36, %37, %38, %39, %40, %41, %42, %43, %44, %45, %46, %47,"
      "%48, %49, %50, %51, %52, %53, %54, %55, %56, %57, %58, %59, %60, %61, %62, %63,"
      "%64, %65, %66, %67, %68, %69, %70, %71, %72, %73, %74, %75, %76, %77, %78, %79,"
      "%80, %81, %82, %83, %84, %85, %86, %87, %88, %89, %90, %91, %92, %93, %94, %95,"
      "%96, %97, %98, %99, %100, %101, %102, %103, %104, %105, %106, %107, %108, %109, %110, %111,"
      "%112, %113, %114, %115, %116, %117, %118, %119, %120, %121, %122, %123, %124, %125, %126, %127"
      "}, %128, %129, p, 1, 1, 0, %131;\n}\n"
      : "+f"(d[0]), "+f"(d[1]), "+f"(d[2]), "+f"(d[3]), "+f"(d[4]), "+f"(d[5]), "+f"(d[6]), "+f"(d[7]),
        "+f"(d[8]), "+f"(d[9]), "+f"(d[10]), "+f"(d[11]), "+f"(d[12]), "+f"(d[13]), "+f"(d[14]), "+f"(d[15]),
        "+f"(d[16]), "+f"(d[17]), "+f"(d[18]), "+f"(d[19]), "+f"(d[20]), "+f"(d[21]), "+f"(d[22]), "+f"(d[23]),
        "+f"(d[24]), "+f"(d[25]), "+f"(d[26]), "+f"(d[27]), "+f"(d[28]), "+f"(d[29]), "+f"(d[30]), "+f"(d[31]),
        "+f"(d[32]), "+f"(d[33]), "+f"(d[34]), "+f"(d[35]), "+f"(d[36]), "+f"(d[37]), "+f"(d[38]), "+f"(d[39]),
        "+f"(d[40]), "+f"(d[41]), "+f"(d[42]), "+f"(d[43]), "+f"(d[44]), "+f"(d[45]), "+f"(d[46]), "+f"(d[47]),
        "+f"(d[48]), "+f"(d[49]), "+f"(d[50]), "+f"(d[51]), "+f"(d[52]), "+f"(d[53]), "+f"(d[54]), "+f"(d[55]),
        "+f"(d[56]), "+f"(d[57]), "+f"(d[58]), "+f"(d[59]), "+f"(d[60]), "+f"(d[61]), "+f"(d[62]), "+f"(d[63]),
        "+f"(d[64]), "+f"(d[65]), "+f"(d[66]), "+f"(d[67]), "+f"(d[68]), "+f"(d[69]), "+f"(d[70]), "+f"(d[71]),
        "+f"(d[72]), "+f"(d[73]), "+f"(d[74]), "+f"(d[75]), "+f"(d[76]), "+f"(d[77]), "+f"(d[78]), "+f"(d[79]),
        "+f"(d[80]), "+f"(d[81]), "+f"(d[82]), "+f"(d[83]), "+f"(d[84]), "+f"(d[85]), "+f"(d[86]), "+f"(d[87]),
        "+f"(d[88]), "+f"(d[89]), "+f"(d[90]), "+f"(d[91]), "+f"(d[92]), "+f"(d[93]), "+f"(d[94]), "+f"(d[95]),
        "+f"(e[0]), "+f"(e[1]), "+f"(e[2]), "+f"(e[3]), "+f"(e[4]), "+f"(e[5]), "+f"(e[6]), "+f"(e[7]),
        "+f"(e[8]), "+f"(e[9]), "+f"(e[10]), "+f"(e[11]), "+f"(e[12]), "+f"(e[13]), "+f"(e[14]), "+f"(e[15]),
        "+f"(e[16]), "+f"(e[17]), "+f"(e[18]), "+f"(e[19]), "+f"(e[20]), "+f"(e[21]), "+f"(e[22]), "+f"(e[23]),
        "+f"(e[24]), "+f"(e[25]), "+f"(e[26]), "+f"(e[27]), "+f"(e[28]), "+f"(e[29]), "+f"(e[30]), "+f"(e[31])
      : "l"(descA), "l"(descB), "r"(scaleD), "n"(TB));
}
template <int TB = 1>
__device__ __forceinline__ void wgmma_ss_n192(float (&d)[96], uint64_t descA, uint64_t descB, int scaleD) {
  asm volatile("{\n.reg .pred p;\nsetp.ne.b32 p, %98, 0;\n"
      "wgmma.mma_async.sync.aligned.m64n192k16.f32.bf16.bf16 {"
      "%0, %1, %2, %3, %4, %5, %6, %7, %8, %9, %10, %11, %12, %13, %14, %15,"
      "%16, %17, %18, %19, %20, %21, %22, %23, %24, %25, %26, %27, %28, %29, %30, %31,"
      "%32, %33, %34, %35, %36, %37, %38, %39, %40, %41, %42, %43, %44, %45, %46, %47,"
      "%48, %49, %50, %51, %52, %53, %54, %55, %56, %57, %58, %59, %60, %61, %62, %63,"
      "%64, %65, %66, %67, %68, %69, %70, %71, %72, %73, %74, %75, %76, %77, %78, %79,"
      "%80, %81, %82, %83, %84, %85, %86, %87, %88, %89, %90, %91, %92, %93, %94, %95"
      "}, %96, %97, p, 1, 1, 0, %99;\n}\n"
      : "+f"(d[0]), "+f"(d[1]), "+f"(d[2]), "+f"(d[3]), "+f"(d[4]), "+f"(d[5]), "+f"(d[6]), "+f"(d[7]),
        "+f"(d[8]), "+f"(d[9]), "+f"(d[10]), "+f"(d[11]), "+f"(d[12]), "+f"(d[13]), "+f"(d[14]), "+f"(d[15]),
        "+f"(d[16]), "+f"(d[17]), "+f"(d[18]), "+f"(d[19]), "+f"(d[20]), "+f"(d[21]), "+f"(d[22]), "+f"(d[23]),
        "+f"(d[24]), "+f"(d[25]), "+f"(d[26]), "+f"(d[27]), "+f"(d[28]), "+f"(d[29]), "+f"(d[30]), "+f"(d[31]),
        "+f"(d[32]), "+f"(d[33]), "+f"(d[34]), "+f"(d[35]), "+f"(d[36]), "+f"(d[37]), "+f"(d[38]), "+f"(d[39]),
        "+f"(d[40]), "+f"(d[41]), "+f"(d[42]), "+f"(d[43]), "+f"(d[44]), "+f"(d[45]), "+f"(d[46]), "+f"(d[47]),
        "+f"(d[48]), "+f"(d[49]), "+f"(d[50]), "+f"(d[51]), "+f"(d[52]), "+f"(d[53]), "+f"(d[54]), "+f"(d[55]),
        "+f"(d[56]), "+f"(d[57]), "+f"(d[58]), "+f"(d[59]), "+f"(d[60]), "+f"(d[61]), "+f"(d[62]), "+f"(d[63]),
        "+f"(d[64]), "+f"(d[65]), "+f"(d[66]), "+f"(d[67]), "+f"(d[68]), "+f"(d[69]), "+f"(d[70]), "+f"(d[71]),
        "+f"(d[72]), "+f"(d[73]), "+f"(d[74]), "+f"(d[75]), "+f"(d[76]), "+f"(d[77]), "+f"(d[78]), "+f"(d[79]),
        "+f"(d[80]), "+f"(d[81]), "+f"(d[82]), "+f"(d[83]), "+f"(d[84]), "+f"(d[85]), "+f"(d[86]), "+f"(d[87]),
        "+f"(d[88]), "+f"(d[89]), "+f"(d[90]), "+f"(d[91]), "+f"(d[92]), "+f"(d[93]), "+f"(d[94]), "+f"(d[95])
      : "l"(descA), "l"(descB), "r"(scaleD), "n"(TB));
}
template <unsigned long long DESC, int SCALE>
__device__ __forceinline__ void wgmma_rs_n56(float (&d)[28], uint32_t a0, uint32_t a1, uint32_t a2, uint32_t a3) {
  asm volatile("{\n.reg .b64 desc;\nmov.b64 desc, %32;\n"
      "wgmma.mma_async.sync.aligned.m64n56k16.f32.bf16.bf16 {"
      "%0, %1, %2, %3, %4, %5, %6, %7, %8, %9, %10, %11, %12, %13, %14, %15,"
      "%16, %17, %18, %19, %20, %21, %22, %23, %24, %25, %26, %27"
      "}, {%28, %29, %30, %31}, desc, %33, 1, 1, 0;\n}\n"
      : "+f"(d[0]), "+f"(d[1]), "+f"(d[2]), "+f"(d[3]), "+f"(d[4]), "+f"(d[5]), "+f"(d[6]), "+f"(d[7]),
        "+f"(d[8]), "+f"(d[9]), "+f"(d[10]), "+f"(d[11]), "+f"(d[12]), "+f"(d[13]), "+f"(d[14]), "+f"(d[15]),
        "+f"(d[16]), "+f"(d[17]), "+f"(d[18]), "+f"(d[19]), "+f"(d[20]), "+f"(d[21]), "+f"(d[22]), "+f"(d[23]),
        "+f"(d[24]), "+f"(d[25]), "+f"(d[26]), "+f"(d[27])
      : "r"(a0), "r"(a1), "r"(a2), "r"(a3), "n"(DESC), "n"(SCALE));
}
template <unsigned long long DESC, int SCALE>
__device__ __forceinline__ void wgmma_rs_n32(float (&d)[28], uint32_t a0, uint32_t a1, uint32_t a2, uint32_t a3) {
  asm volatile("{\n.reg .b64 desc;\nmov.b64 desc, %20;\n"
      "wgmma.mma_async.sync.aligned.m64n32k16.f32.bf16.bf16 {"
      "%0, %1, %2, %3, %4, %5, %6, %7, %8, %9, %10, %11, %12, %13, %14, %15"
      "}, {%16, %17, %18, %19}, desc, %21, 1, 1, 0;\n}\n"
      : "+f"(d[0]), "+f"(d[1]), "+f"(d[2]), "+f"(d[3]), "+f"(d[4]), "+f"(d[5]), "+f"(d[6]), "+f"(d[7]),
        "+f"(d[8]), "+f"(d[9]), "+f"(d[10]), "+f"(d[11]), "+f"(d[12]), "+f"(d[13]), "+f"(d[14]), "+f"(d[15])
      : "r"(a0), "r"(a1), "r"(a2), "r"(a3), "n"(DESC), "n"(SCALE));
}

constexpr int NB = 4096, NF = 26, DIN = 1664;
constexpr int NGEMM = 128, NEXTRA = 4, GRID = NGEMM + NEXTRA;
constexpr int NR = 2;
constexpr int NC_WG0 = 16;
constexpr int WK = 1;
constexpr int OB = 5;
constexpr int AR = 3;
constexpr int MU = 13;
constexpr int HK = 3;
constexpr int PE0 = 14;
constexpr int WD = 2;
constexpr int GI = 3;
constexpr int PE1 = 6;
constexpr int PE2 = 12;
constexpr int PS2 = 11;
constexpr int PS = 6;
constexpr int RB = 4;
constexpr int NC_GEMM = 29, NBIG = 16 * NR, POOL = NGEMM * NC_GEMM, NC_EXTRA = (NB - POOL - NBIG) / NEXTRA;
static_assert((NR == 1 || NR == 2) && NC_WG0 == 16, "split");
constexpr int CW_MAIN = 22 * 1792, CW_LIN = 2 * 1024, CW_BYTES = CW_MAIN + CW_LIN;
constexpr int XSLOT = 4096;

constexpr int UNIT = 8192, FS = 18;
constexpr int U_W = 6, U_XB = 18, U_SP = 24;
constexpr int CW_CUT = 9;
constexpr int OFF_CW = 0, OFF_CW2 = 6 * UNIT, OFF_CWL = 9 * UNIT;
constexpr int OFF_PART = OFF_CWL + CW_LIN;
constexpr int CROW = 528;
constexpr int OFF_CIN = 2 * UNIT;
constexpr int OFF_GIDX = 26 * UNIT;
constexpr int OFF_TIDX = OFF_GIDX + 128 * NF * 4 - 8 * 64 * 4;
constexpr int OFF_CIDX = OFF_GIDX + 128 * NF * 4;
constexpr int OFF_EPI = OFF_CIDX + 30 * NF * 4;
constexpr int OFF_DNN = OFF_EPI + 128 * 16;
constexpr int OFF_BAR = OFF_DNN + 96 * 4;
constexpr int SMEM_BYTES = OFF_BAR + 66 * 8;
static_assert(CW_CUT * 1792 <= 2 * UNIT && (22 - CW_CUT) * 1792 <= 3 * UNIT && 30 * CROW <= 2 * UNIT, "smem");
constexpr uint32_t SMEM_BASE = 1024;
static_assert(SMEM_BYTES <= 232448, "smem");
static_assert(OFF_EPI % 16 == 0 && OFF_CIDX % 16 == 0 && OFF_BAR % 8 == 0, "align");
constexpr int XOFF_W3 = 0, XOFF_W2 = 35152, XOFF_W1 = 70304, XOFF_M = XOFF_W1 + 7 * 1392, XOFF_TAB = XOFF_M + 32 * 40 * 4, XOFF_S = XOFF_TAB + 3072,
              XOFF_SLOT = 10 * UNIT, XOFF_CIN0 = 2 * UNIT, XOFF_CIN1 = 18 * UNIT, XOFF_CIDX = 22 * UNIT;
static_assert(XOFF_S + 7 * 3152 <= 21 * UNIT && 46 * CROW <= 3 * UNIT, "smem");

constexpr int BAR_WIN = 7,
              BAR_FULL = 8,
              BAR_EV = 16,
              BAR_CW = 24,
              BAR_GIDX = 25, BAR_CIDX = 26,
              BAR_W0 = 27,
              BAR_DNN = 28,
              BAR_T = 29,
              BAR_GDONE = 30,
              BAR_PART = 31,
              BAR_CFULL = 32,
              BAR_POOL = BAR_CFULL + 28,
              BAR_C0 = 64;
constexpr int EV_CW = 29, EV_CIN = 30, EV_SLOT = 31, EV_END = 33;
__device__ __forceinline__ uint32_t ev_bar(uint32_t bars, int e) { return bars + 8 * (BAR_EV + (e & 7)); }
__device__ __forceinline__ uint32_t ev_par(int e) { return (e >> 3) & 1; }
__host__ __device__ constexpr int b_x(int t) { return ((0xb2c1430bu >> (4 * t)) & 15) * 2; }
__host__ __device__ constexpr int b_w(int t) { return (0x0d0a120eu >> (8 * (t & 3))) & 31; }
__host__ __device__ constexpr int b_ws(int t) { return (t & 3) == 3 ? 4 : 1; }

struct Scratch {
  uint4 cw[CW_BYTES / 16];
  float part[8 * NB];
  unsigned dflag[16 * 8];
  unsigned epoch[GRID];
  unsigned place[16 * 8];
  unsigned foldflag;
};
__device__ __align__(128) Scratch g_scratch;
struct GPtr { Scratch* s; const uint4* tab; const uint4* jobs; uint32_t zero; };

__device__ __forceinline__ void wg_fence() { asm volatile("wgmma.fence.sync.aligned;" ::: "memory"); }
__device__ __forceinline__ void wg_commit() { asm volatile("wgmma.commit_group.sync.aligned;" ::: "memory"); }
template <int N> __device__ __forceinline__ void wg_wait() { asm volatile("wgmma.wait_group.sync.aligned %0;" ::"n"(N) : "memory"); }
__device__ __forceinline__ uint64_t mkdesc(uint32_t addr, uint32_t lbo, uint32_t sbo, uint32_t swz) {
  return (uint64_t)((addr & 0x3FFFF) >> 4) | ((uint64_t)(lbo >> 4) << 16) | ((uint64_t)(sbo >> 4) << 32) | ((uint64_t)swz << 62);
}
__device__ __forceinline__ bool elect1() {
  uint32_t p; asm volatile("{\n.reg .pred p;\nelect.sync _|p, 0xffffffff;\nselp.b32 %0, 1, 0, p;\n}" : "=r"(p)); return p;
}
__device__ __forceinline__ int fresh(int v) { asm volatile("" : "+r"(v)); return v; }
__device__ __forceinline__ void sched_fence() { asm volatile("pmevent 0;" ::: "memory"); }
__device__ __forceinline__ void mbar_init(uint32_t bar, uint32_t cnt) { asm volatile("mbarrier.init.shared::cta.b64 [%0], %1;" ::"r"(bar), "r"(cnt) : "memory"); }
__device__ __forceinline__ void mbar_arrive(uint32_t bar) { asm volatile("mbarrier.arrive.shared::cta.b64 _, [%0];" ::"r"(bar) : "memory"); }
__device__ __forceinline__ void mbar_arrive_cta(uint32_t bar, uint32_t cta) {
  asm volatile("{\n.reg .b32 r;\nmapa.shared::cluster.u32 r, %0, %1;\nmbarrier.arrive.shared::cluster.b64 _, [r];\n}" ::"r"(bar), "r"(cta) : "memory");
}
__device__ __forceinline__ void mbar_expect_tx(uint32_t bar, uint32_t bytes) { asm volatile("mbarrier.arrive.expect_tx.shared::cta.b64 _, [%0], %1;" ::"r"(bar), "r"(bytes) : "memory"); }
__device__ __forceinline__ void mbar_wait(uint32_t bar, uint32_t parity) {
  asm volatile("{\n.reg .pred p;\nLAB_WAIT:\nmbarrier.try_wait.parity.shared::cta.b64 p, [%0], %1;\n@!p bra LAB_WAIT;\n}" ::"r"(bar), "r"(parity) : "memory");
}
__device__ __forceinline__ void flag_wait(const unsigned* p, unsigned target, unsigned sleep_ns) {
  asm volatile("{\n.reg .pred p;\n.reg .u32 n, v;\nmov.u32 n, 0;\nLAB_WAIT:\n"
               "ld.acquire.gpu.global.u32 v, [%0];\n"
               "sub.u32 v, v, %1;\n"
               "setp.ge.s32 p, v, 0;\n"
               "@p bra DONE;\n"
               "nanosleep.u32 %2;\n"
               "add.u32 n, n, 1;\n"
               "setp.lt.u32 p, n, 400000;\n"
               "@p bra LAB_WAIT;\n"
               "DONE:\n}" ::"l"(p), "r"(target), "r"(sleep_ns) : "memory");
}
__device__ __forceinline__ void flag_add(unsigned* p) { asm volatile("red.release.gpu.global.add.u32 [%0], 1;" ::"l"(p) : "memory"); }
__device__ __forceinline__ void tma_load(uint32_t dst, const CUtensorMap* tm, int c0, int c1, uint32_t bar) {
  asm volatile("cp.async.bulk.tensor.2d.shared::cluster.global.mbarrier::complete_tx::bytes [%0], [%1, {%3, %4}], [%2];"
               ::"r"(dst), "l"(tm), "r"(bar), "r"(c0), "r"(c1) : "memory");
}
__device__ __forceinline__ void tma_row_mc(uint32_t dst, const CUtensorMap* tm, int row, uint32_t bar) {
  asm volatile("cp.async.bulk.tensor.2d.shared::cluster.global.mbarrier::complete_tx::bytes.multicast::cluster [%0], [%1, {%3, %4}], [%2], %5;"
               ::"r"(dst), "l"(tm), "r"(bar), "r"(0), "r"(row), "h"((uint16_t)3));
}
__device__ __forceinline__ void tma_row(uint32_t dst, const CUtensorMap* tm, int row, uint32_t bar) {
  asm volatile("cp.async.bulk.tensor.2d.shared::cluster.global.mbarrier::complete_tx::bytes [%0], [%1, {%3, %4}], [%2];"
               ::"r"(dst), "l"(tm), "r"(bar), "r"(0), "r"(row));
}
__device__ __forceinline__ void bulk_load(uint32_t dst, const void* src, uint32_t bytes, uint32_t bar) {
  asm volatile("cp.async.bulk.shared::cluster.global.mbarrier::complete_tx::bytes [%0], [%1], %2, [%3];"
               ::"r"(dst), "l"(src), "r"(bytes), "r"(bar));
}
__device__ __forceinline__ void l2_prefetch(const void* src, uint32_t bytes) {
  asm volatile("cp.async.bulk.prefetch.L2.global [%0], %1;" ::"l"(src), "r"(bytes));
}
__device__ __forceinline__ void w_prefetch(const __nv_bfloat16* w1, int f, int cta, int piece) {
  l2_prefetch(w1 + (f * 64 + (cta >> 3) * 4 + (cta & 1) * 2 + (piece & 1)) * DIN + (piece < 2 ? (cta & 6) * 192 : 1536 + (cta & 4) * 16),
              piece < 2 ? 768 : 128);
}
__device__ __forceinline__ void cpasync16(uint32_t dst, const void* src) {
  asm volatile("cp.async.cg.shared.global [%0], [%1], 16;" ::"r"(dst), "l"(src) : "memory");
}
template <int ID, int N> __device__ __forceinline__ void bar_sync() { asm volatile("bar.sync %0, %1;" ::"n"(ID), "n"(N) : "memory"); }
template <int ID, int N> __device__ __forceinline__ void bar_arrive() { asm volatile("bar.arrive %0, %1;" ::"n"(ID), "n"(N) : "memory"); }
__device__ __forceinline__ void ldsm4t(uint32_t& a, uint32_t& b, uint32_t& c, uint32_t& d, uint32_t addr) {
  asm volatile("ldmatrix.sync.aligned.m8n8.x4.trans.shared.b16 {%0,%1,%2,%3}, [%4];" : "=r"(a), "=r"(b), "=r"(c), "=r"(d) : "r"(addr) : "memory");
}
__device__ __forceinline__ void ldsm2t(uint32_t& a, uint32_t& b, uint32_t addr) {
  asm volatile("ldmatrix.sync.aligned.m8n8.x2.trans.shared.b16 {%0,%1}, [%2];" : "=r"(a), "=r"(b) : "r"(addr) : "memory");
}
__device__ __forceinline__ int lds32(uint32_t addr) { int v; asm volatile("ld.shared.b32 %0, [%1];" : "=r"(v) : "r"(addr)); return v; }
__device__ __forceinline__ int2 lds64(uint32_t addr) { int2 v; asm volatile("ld.shared.v2.b32 {%0,%1}, [%2];" : "=r"(v.x), "=r"(v.y) : "r"(addr)); return v; }
__device__ __forceinline__ int4 lds128(uint32_t addr) {
  int4 v; asm volatile("ld.shared.v4.b32 {%0,%1,%2,%3}, [%4];" : "=r"(v.x), "=r"(v.y), "=r"(v.z), "=r"(v.w) : "r"(addr)); return v;
}
__device__ __forceinline__ float4 lds128f(uint32_t addr) {
  float4 v; asm volatile("ld.shared.v4.f32 {%0,%1,%2,%3}, [%4];" : "=f"(v.x), "=f"(v.y), "=f"(v.z), "=f"(v.w) : "r"(addr) : "memory"); return v;
}
__device__ __forceinline__ void sts32f(uint32_t addr, float v) { asm volatile("st.shared.f32 [%0], %1;" ::"r"(addr), "f"(v) : "memory"); }
__device__ __forceinline__ float bf_lo(uint32_t v) { return __uint_as_float(v << 16); }
__device__ __forceinline__ float bf_hi(uint32_t v) { return __uint_as_float(v & 0xffff0000u); }
__device__ __forceinline__ float bf2f(__nv_bfloat16 v) { return __bfloat162float(v); }

__device__ __forceinline__ uint32_t mul2(uint32_t a, uint32_t b) {
  uint32_t r; asm volatile("mul.rn.bf16x2 %0, %1, %2;" : "=r"(r) : "r"(a), "r"(b)); return r;
}
__device__ __forceinline__ uint32_t mul2lo(uint32_t a, uint32_t b) {
  uint32_t r;
  asm volatile("{\n.reg .b16 l, h;\n.reg .b32 t;\nmov.b32 {l, h}, %2;\nmov.b32 t, {l, l};\nmul.rn.bf16x2 %0, %1, t;\n}" : "=r"(r) : "r"(a), "r"(b));
  return r;
}
__device__ __forceinline__ uint32_t mul2hi(uint32_t a, uint32_t b) {
  uint32_t r;
  asm volatile("{\n.reg .b16 l, h;\n.reg .b32 t;\nmov.b32 {l, h}, %2;\nmov.b32 t, {h, h};\nmul.rn.bf16x2 %0, %1, t;\n}" : "=r"(r) : "r"(a), "r"(b));
  return r;
}

__host__ __device__ constexpr int xfield(int r, int e, int c) {
  return r == 9 ? 24 + e : 8 * (r / 3) + 2 * (((r % 3) + c) & 3) + (((r % 3) == 2 && c >= 2) ? 1 - e : e);
}
__host__ __device__ constexpr int blk_a(int b) { return b < 12 ? 3 * (b / 8) + ((b & 3) == 3) : (b < 15 ? 3 * (b - 12) : 3 * (b - 15)); }
__host__ __device__ constexpr int blk_b(int b) { return b < 12 ? 3 * (b < 4 ? 1 : 2) + ((b & 3) == 3 ? 0 : (b & 3)) : (b < 15 ? 3 * (b - 12) + 1 : 9); }
__host__ __device__ constexpr int slot_pq(int u, int e, int c) {
  return u < 36 ? (xfield(blk_a(u >> 1), e, c) | (xfield(blk_b(u >> 1), u & 1, c) << 8))
       : u < 39 ? (xfield(3 * (u - 36), e, c) | (xfield(3 * (u - 36), 0, c) << 8))
       : u < 42 ? (xfield(3 * (u - 39), e, c) | (xfield(3 * (u - 39) + 2, e, c) << 8))
       : u == 42 ? (xfield(3 * e, 1, c) * 257)
       : u == 43 ? (e == 0 ? (xfield(6, 1, c) * 257)
                           : (c == 0 ? 24 * 257 : c == 1 ? 25 * 257 : c == 2 ? (24 | 25 << 8) : 26 * 257))
       : u < 47 ? (xfield(3 * (u - 44), e, c) | (26 << 8))
       : (c == 0 ? ((24 + e) | 26 << 8) : c == 3 ? ((26 + e) | (27 - e) << 8) : 27 * 257);
}
struct SlotTab { uint32_t v[2 * 48 * 8]; };
constexpr SlotTab make_slot_tab() {
  SlotTab t{};
  for (int u = 0; u < 48; u++)
    for (int k = 0; k < 8; k++) {
      const int pq = slot_pq(u, k & 1, k >> 1), p = pq & 255, q = pq >> 8;
      t.v[u * 8 + k] = (uint32_t)((p * 28 + q) * 4) | ((uint32_t)(((p != q && q < 26) ? q * 28 + p : 27 * 28 + 27) * 4) << 16);
      t.v[384 + u * 8 + k] = (uint32_t)(q < 26 ? (p * 26 + q) * 2 : 1360) | ((uint32_t)((p != q && q < 26) ? (q * 26 + p) * 2 : 1360) << 16);
    }
  return t;
}
__device__ __align__(16) const SlotTab g_slot_tab = make_slot_tab();

struct CinCtx {
  uint32_t tab0, tab1, full, fmask, it, lim, co, sb;
  uint32_t cin, o03, o14, o25, o9, o78, selA, selB;
  bool ones, lead;
};
constexpr unsigned long long CW_DESC = (unsigned long long)((SMEM_BASE + OFF_CW) >> 4) | (8ull << 16) | (16ull << 32);
constexpr int OFF_INIT = U_SP * UNIT;
constexpr unsigned long long INIT_DESC = (unsigned long long)((SMEM_BASE + OFF_INIT) >> 4) | (9ull << 32);
constexpr unsigned long long ONES_DESC = (SMEM_BASE + OFF_INIT + 4608) >> 4;
constexpr unsigned long long CWL_DESC = CW_DESC + (OFF_CWL - OFF_CW) / 16;

template <int U>
__device__ __forceinline__ uint32_t zreg(uint32_t (&x)[11][2], int h, const CinCtx& c) {
  if constexpr (U < 36) {
    if constexpr (U & 1) return mul2hi(x[blk_a(U >> 1)][h], x[blk_b(U >> 1)][h]);
    else return mul2lo(x[blk_a(U >> 1)][h], x[blk_b(U >> 1)][h]);
  } else if constexpr (U < 39) {
    return mul2lo(x[3 * (U - 36)][h], x[3 * (U - 36)][h]);
  } else if constexpr (U < 42) {
    return mul2(x[3 * (U - 39)][h], x[3 * (U - 39) + 2][h]);
  } else if constexpr (U == 42) {
    const uint32_t p = __byte_perm(x[0][h], x[3][h], 0x7632);
    return mul2(p, p);
  } else {
    x[10][h] = c.ones ? 0x3f803f80u : x[9][h];
    return mul2(__byte_perm(x[6][h], x[10][h], c.selA), __byte_perm(x[6][h], x[10][h], c.selB));
  }
}

__host__ __device__ constexpr int kord(int s) { return s == 0 ? 21 : s < 4 ? 14 + s : s < 19 ? s - 4 : s - 1; }
template <int S0, int NS>
struct ZGroup {
  uint32_t z[NS][4];
  template <int I = 0>
  __device__ __forceinline__ void fill(uint32_t (&x)[11][2], const CinCtx& c) {
    if constexpr (I < NS) {
      z[I][0] = zreg<2 * kord(S0 + I)>(x, 0, c);
      z[I][1] = zreg<2 * kord(S0 + I)>(x, 1, c);
      z[I][2] = zreg<2 * kord(S0 + I) + 1>(x, 0, c);
      z[I][3] = zreg<2 * kord(S0 + I) + 1>(x, 1, c);
      fill<I + 1>(x, c);
    }
  }
  template <int I = 0>
  __device__ __forceinline__ void mma(float (&acc)[28]) {
    if constexpr (I < NS) {
      constexpr int S = kord(S0 + I);
      wgmma_rs_n56<CW_DESC + (S < CW_CUT ? S * 1792 : OFF_CW2 - OFF_CW + (S - CW_CUT) * 1792) / 16, (S0 + I) != 0>(acc, z[I][0], z[I][1], z[I][2], z[I][3]);
      mma<I + 1>(acc);
    }
  }
};

__device__ __forceinline__ void cin_finish(const CinCtx& c, float (&acc)[28], uint32_t out) {
#pragma unroll
  for (int i = 0; i < 28; i++) asm volatile("" : "+f"(acc[i]));
  float s0 = acc[12] * acc[13], s1 = acc[14] * acc[15];
#pragma unroll
  for (int i = 0; i < 12; i += 2) {
    s0 = fmaf(acc[i], acc[16 + i], s0);
    s1 = fmaf(acc[i + 1], acc[17 + i], s1);
  }
  sts32f(out, s0 + s1);
}

__device__ __forceinline__ void cin_ldsm(const CinCtx& c, uint32_t so, uint32_t (&x)[11][2], int i) {
  if (i == 0) ldsm4t(x[0][0], x[0][1], x[3][0], x[3][1], so + c.o03);
  if (i == 1) ldsm2t(x[6][0], x[6][1], so + c.o03 + 2048);
  if (i == 1) ldsm2t(x[9][0], x[9][1], so + c.o9 + 3072);
  if (i == 2) ldsm4t(x[1][0], x[1][1], x[4][0], x[4][1], so + c.o14);
  if (i == 3) ldsm4t(x[2][0], x[2][1], x[5][0], x[5][1], so + c.o25);
  if (i == 4) ldsm4t(x[7][0], x[7][1], x[8][0], x[8][1], so + c.o78 + 2048);
}
__device__ __forceinline__ bool cin_late(const CinCtx& c, int k) {
  uint32_t ok = 1;
  asm volatile("{\n.reg .pred p;\nmbarrier.test_wait.parity.shared::cta.b64 p, [%1], %2;\nselp.b32 %0, 1, 0, p;\n}"
               : "=r"(ok) : "r"(c.full + (c.it & c.fmask) + 8 * k), "r"((((c.it & ~c.fmask) << 25) ^ (c.lim - 9 - 8 * k - c.it)) >> 31) : "memory");
  return !ok;
}
__device__ __forceinline__ void cin_load(const CinCtx& c, int k, bool late, uint32_t (&x)[11][2]) {
  const uint32_t fb = c.full + (c.it & c.fmask) + 8 * k;
  if (__builtin_expect(late, 0)) mbar_wait(fb, ((c.it & ~c.fmask) >> 6) & 1);
#pragma unroll
  for (int i = 0; i < 5; i++) cin_ldsm(c, c.sb + (c.tab0 & 31) * UNIT + k * XSLOT, x, i);
  if (c.lead) mbar_arrive(fb + 64);
}
__device__ __forceinline__ void cin_advance(CinCtx& c) {
  const uint32_t t = __funnelshift_r(c.tab0, c.tab1, 8);
  c.tab1 = __funnelshift_r(c.tab1, c.tab0, 8);
  c.tab0 = t;
  c.it += 16;
  c.co += 2 * CROW;
}
constexpr int CG_SIZE = 2;
constexpr int CG_WAIT = 4;
constexpr int CG_HEAD = 4;
constexpr int CG_LOAD = 4;
constexpr int CG_N = (22 + CG_SIZE - 1) / CG_SIZE;
constexpr int CG_ASK = 4;
constexpr int CG_HW = 3;
template <int G, int GEND>
__device__ __forceinline__ void cin_groups(const CinCtx& c, uint32_t (&x)[11][2], float (&acc)[28],
                                           int q, bool& late, uint32_t (&xn)[11][2]) {
  if constexpr (G < GEND) {
    constexpr int S0 = G * CG_SIZE, NS = (S0 + CG_SIZE <= 22) ? CG_SIZE : 22 - S0;
    if constexpr (G == CG_ASK) late = cin_late(c, q);
    ZGroup<S0, NS> g; g.fill(x, c);
    wg_fence();
    g.mma(acc);
    wg_commit();
    if constexpr (G == CG_N - 1) {
      wg_fence();
      wgmma_rs_n32<CWL_DESC, 1>(acc, x[0][0], x[0][1], x[3][0], x[3][1]);
      wgmma_rs_n32<CWL_DESC + 1024 / 16, 1>(acc, x[6][0], x[6][1], x[10][0], x[10][1]);
      wg_commit();
    }
    if constexpr (G == CG_LOAD) cin_load(c, q, late, xn);
    if constexpr (G != CG_HEAD - 1) {
      if constexpr (G == CG_N - 1 || G < CG_HW) wg_wait<CG_WAIT + 1>(); else wg_wait<CG_WAIT>();
    }
    cin_groups<G + 1, GEND>(c, x, acc, q, late, xn);
  }
}
__device__ __forceinline__ void cin_head(const CinCtx& c, uint32_t (&x)[11][2], float (&acc)[28], int q, bool& late) {
  cin_groups<0, CG_HEAD>(c, x, acc, q, late, x);
}
__device__ __forceinline__ void cin_tail(const CinCtx& c, uint32_t (&x)[11][2], float (&acc)[28],
                                         int q, bool& late, uint32_t (&xn)[11][2]) {
  cin_groups<CG_HEAD, CG_N>(c, x, acc, q, late, xn);
}

__device__ __forceinline__ void cin_setup(CinCtx& c, uint32_t sb, int wg, int tid, bool gemm, int nj) {
  c.tab0 = !gemm ? 0x0d0c0b0a + wg * 0x04040404 : wg ? 0x0d0c0b0a : 0x100f0e1a;
  c.tab1 = !gemm ? c.tab0 : wg ? 0x17171615 : 0x14131211;
  c.full = sb + OFF_BAR + 8 * (BAR_CFULL + wg * 16);
  c.fmask = gemm ? 0x70 : 0x30;
  c.it = 0; c.lim = 8 * nj; c.sb = sb;
  c.lead = (tid & 31) == 0 && !gemm;
  const uint32_t f0 = tid & 7, ch = (tid & 0x60) | ((tid & 8) << 1), chm = ch | ((tid & 16) << 6);
  c.o03 = (f0 * 144) ^ chm;
  c.o14 = (((f0 + 2) & 7) * 144) ^ chm;
  c.o25 = c.o03 ^ (tid & 4 ? 5 * 144 : 4 * 144);
  c.o9 = ((tid & 1) * 144) ^ ch;
  c.o78 = tid & 16 ? c.o25 - 1024 : c.o14;
  const int q = tid & 3;
  c.selA = q == 1 ? 0x7632 : 0x5432;
  c.selB = q == 0 ? 0x5432 : 0x7632;
  c.ones = q == 3;
}
template <typename F0, typename F, typename F2>
__device__ __forceinline__ void cin_run(CinCtx& c, F0 first_load, F after_start, F2 before_end) {
  float accA[28], accB[28];
  uint32_t xA[11][2], xB[11][2];
  first_load(xA);
  bool late;
  cin_head(c, xA, accA, 0, late);
  after_start();
#pragma unroll 1
  for (;;) {
    const uint32_t out = c.cin + c.co;
    cin_tail(c, xA, accA, 0, late, xB);
    if (c.it + 8 >= c.lim) { before_end(); wg_wait<0>(); cin_finish(c, accA, out); break; }
    cin_head(c, xB, accB, 1, late);
    wg_wait<CG_HEAD>();
    cin_finish(c, accA, out);
    cin_tail(c, xB, accB, 1, late, xA);
    cin_advance(c);
    if (c.it >= c.lim) { before_end(); wg_wait<0>(); cin_finish(c, accB, out + CROW); break; }
    cin_head(c, xA, accA, 0, late);
    wg_wait<CG_HEAD>();
    cin_finish(c, accB, out + CROW);
  }
}

constexpr float ALPHA = 0.3292034911525734f, KAPPA = 2.423681954311584f;

constexpr int GD = 1;
constexpr int GK = 0;
constexpr int TK = 2;
constexpr int GL = 2;
template <int NG>
struct Gelu {
  float4 q[NG / 2];
  float u[4 * NG];
  float ab;
  uint32_t ep;
  static constexpr int END = NG + GD + 4;
  __device__ __forceinline__ void start(uint32_t a, uint32_t sb) {
    ep = a;
    ab = __int_as_float(lds32(sb + OFF_EPI + 1024));
  }
  __device__ __forceinline__ void take(const Gelu& o) {
#pragma unroll
    for (int m = TK; m < NG / 2; m++)
      asm volatile("mov.b32 %0, %4;\nmov.b32 %1, %5;\nmov.b32 %2, %6;\nmov.b32 %3, %7;"
                   : "=f"(q[m].x), "=f"(q[m].y), "=f"(q[m].z), "=f"(q[m].w) : "f"(o.q[m].x), "f"(o.q[m].y), "f"(o.q[m].z), "f"(o.q[m].w));
    ab = o.ab;
  }
  struct Nop { __device__ __forceinline__ void operator()(int) const {} };
  template <int I0, int I1, bool LOAD = true, typename F = Nop>
  __device__ __forceinline__ void part(float (&d)[4 * NG], float& r0, float& r1, F hook = F()) {
#pragma unroll
    for (int i = I0; i < I1; i++) {
      sched_fence();
      hook(i - I0);
#pragma unroll
      for (int m = 0; m < NG / 2; m++)
        if ((LOAD || m < TK) && i == 2 * m + GD + 4 - (m < 2 ? 2 : GL)) q[m] = lds128f(ep + m * 64);
#pragma unroll
      for (int e = 0; e < 4; e++) {
        const int k0 = 4 * i + e, k1 = k0 - 4, k2 = k0 - 8, k3 = k0 - 12, k4 = k3 - 4 * GD, k5 = k4 - 4;
        if (k3 >= 0 && k3 < 4 * NG) asm volatile("tanh.approx.f32 %0, %0;" : "+f"(u[k3]));
        if (k5 >= 0) {
          const float4 v = q[k5 >> 3];
          float& r = e & 2 ? r1 : r0;
          asm volatile("fma.rn.f32 %0, %1, %2, %0;" : "+f"(r) : "f"(d[k5]), "f"(k5 & 4 ? (e & 1 ? v.w : v.z) : (e & 1 ? v.y : v.x)));
        }
        if (k4 >= 0 && k4 < 4 * NG) asm volatile("fma.rn.f32 %0, %0, %1, %0;" : "+f"(d[k4]) : "f"(u[k4]));
        if (k2 >= 0 && k2 < 4 * NG) asm volatile("mul.rn.f32 %0, %0, %1;" : "+f"(u[k2]) : "f"(d[k2]));
        if (k1 >= 0 && k1 < 4 * NG) asm volatile("fma.rn.f32 %0, %1, %1, %2;" : "=f"(u[k1]) : "f"(d[k1]), "f"(KAPPA));
        if (k0 < 4 * NG) asm volatile("fma.rn.f32 %0, %0, %1, %2;" : "+f"(d[k0]) : "f"(ALPHA), "f"(ab));
      }
    }
    sched_fence();
  }
};
__device__ __forceinline__ void pin(float a, float b, uint32_t addr, uint32_t zero) {
  asm volatile("{\n.reg .pred p;\nsetp.ne.u32 p, %3, 0;\n@p st.shared.v2.f32 [%0], {%1, %2};\n}" ::"r"(addr), "f"(a), "f"(b), "r"(zero) : "memory");
}
__device__ __forceinline__ void hand_on(float (&d)[96], const float (&s)[96]) {
#pragma unroll
  for (int i = 0; i < 96; i++) asm volatile("mov.b32 %0, %1;" : "=f"(d[i]) : "f"(s[i]));
}
__device__ __forceinline__ uint64_t desc_x(int u) { return mkdesc(SMEM_BASE, 16, 1024, 1) + u * (UNIT / 16); }
__device__ __forceinline__ uint64_t desc_w(int u, int stride = 1) { return mkdesc(SMEM_BASE, stride * UNIT, 1024, 1) + u * (UNIT / 16); }
__device__ __forceinline__ void tile_step(float (&d)[96], uint64_t dA, uint64_t dB) {
  wg_fence();
#pragma unroll
  for (int k = 0; k < 4; k++) wgmma_ss_n192(d, dA + 2 * k, dB + 128 * k, 1);
  wg_commit();
}
template <int K0 = 0, int K1 = 4>
__device__ __forceinline__ void wide_step(float (&d)[96], float (&e)[32], uint64_t dA, uint64_t dB) {
  wg_fence();
#pragma unroll
  for (int k = K0; k < K1; k++) wgmma_ss_n256(d, e, dA + 2 * k, dB + 128 * k, 1);
  wg_commit();
}
constexpr int slot_of(int wg, int j) {
  return wg ? (j == 0 ? 24 * UNIT : j <= 8 ? 10 * UNIT + (j - 1) * XSLOT : 21 * UNIT + (j - 9) * XSLOT)
            : (j == 0 ? OFF_GIDX + 2 * XSLOT : (j < 3 ? OFF_GIDX + 2 * XSLOT : 14 * UNIT) + (j - 3) * XSLOT);
}
constexpr int NLW = 3;
constexpr int NE = 10;
constexpr int LB = 1;
struct alignas(8) Job { uint32_t wait, par, slot, full, idx, next; };
constexpr int OFF_WIN = OFF_EPI + 1028, OFF_JOB = OFF_EPI + 1040, OFF_PIDX = OFF_JOB + 32 * sizeof(Job), XOFF_JOB = 24 * UNIT, XOFF_DNN = 25 * UNIT;
static_assert(OFF_PIDX + 2 * NF * 4 <= OFF_DNN, "smem");
struct JobTab { Job v[2][32 + NC_EXTRA]; };
constexpr Job make_job(int rank, int wait, int par, int slot, int full, int idx, int next) {
  const uint32_t sb = SMEM_BASE + (rank << 24);
  return Job{sb + OFF_BAR + 8 * wait, uint32_t(par), sb + slot, sb + OFF_BAR + 8 * full, sb + idx, next ? sb + next : 0};
}
constexpr JobTab make_jobs() {
  JobTab t{};
  int m = 0;
  for (int n = 0; n < 36; n++) {
    const int wg = n < 7 ? n == 4 : n & 1, j = n < 4 ? n : n < 7 ? n - 1 - 3 * wg : wg ? n / 2 - 2 : n / 2 + 2, s = wg * NC_WG0 + j;
    if (s >= NC_GEMM + NR || j >= NC_WG0) continue;
    const int e = n < 7 ? EV_SLOT : EV_END;
    for (int odd = 0; odd < 2; odd++)
      t.v[odd][m] = make_job(odd, n < 3 ? BAR_GDONE : n < NE ? BAR_EV + (e & 7) : BAR_PART, n < 3 ? 0 : (e >> 3) & 1, s > NC_GEMM ? 25 * UNIT : slot_of(wg, j),
                                   s >= NC_GEMM ? BAR_POOL : j ? BAR_CFULL + wg * 16 + j - 1 : BAR_C0 + wg,
                                   s >= NC_GEMM ? OFF_PIDX + (s - NC_GEMM + (NR == 1 && odd)) * NF * 4 : OFF_CIDX + (s + odd) * NF * 4,
                             m + NLW < NC_GEMM + NR ? OFF_JOB + (m + NLW) * sizeof(Job) : 0);
    m++;
  }
  for (int n = 0; n < NC_EXTRA; n++) {
    const int wg = n & 1, j = n >> 1, bi = (j - 1) & 7;
    for (int odd = 0; odd < 2; odd++)
      t.v[odd][32 + n] = make_job(odd, j == 0 ? BAR_GDONE : j <= 8 ? BAR_EV + (EV_END & 7) : BAR_CFULL + wg * 16 + 8 + bi, j <= 8 ? 0 : (((j - 1) >> 3) & 1) ^ 1,
                           j ? XOFF_SLOT + (wg * 8 + bi) * XSLOT : OFF_GIDX + wg * XSLOT, j ? BAR_CFULL + wg * 16 + bi : BAR_C0 + wg,
                           XOFF_CIDX + (wg * NC_EXTRA / 2 + j) * NF * 4, n + 4 < NC_EXTRA ? XOFF_JOB + (n + 4) * sizeof(Job) : 0);
  }
  return t;
}
__device__ __align__(16) const JobTab g_jobs = make_jobs();
static_assert(((EV_END >> 3) & 1) == 0, "parity");

__device__ __forceinline__ int cin_start(int c) { return c < NGEMM ? c * NC_GEMM : NB - (GRID - c) * NC_EXTRA; }
__device__ __forceinline__ int group_of(int c) { return (c < 8 ? 4 + (c >> 1) : c < 72 ? (c - 8) >> 4 : (c - 16) / 14) * 2 + (c & 1); }

__device__ __forceinline__ int fold_i0(int e) { return e < 2 ? 7 * e : 2 + 6 * e; }
__device__ __forceinline__ uint32_t ldg16(const void* p) { uint16_t v; asm volatile("ld.global.nc.u16 %0, [%1];" : "=h"(v) : "l"(p)); return v; }
__device__ __forceinline__ uint32_t ldg32(const void* p) { uint32_t v; asm volatile("ld.global.nc.u32 %0, [%1];" : "=r"(v) : "l"(p)); return v; }
__device__ __forceinline__ uint4 ldg128(const void* p) {
  uint4 v; asm volatile("ld.global.nc.v4.u32 {%0,%1,%2,%3}, [%4];" : "=r"(v.x), "=r"(v.y), "=r"(v.z), "=r"(v.w) : "l"(p)); return v;
}
__device__ __forceinline__ void sts64f(uint32_t addr, float a, float b) { asm volatile("st.shared.v2.f32 [%0], {%1, %2};" ::"r"(addr), "f"(a), "f"(b) : "memory"); }
__device__ __forceinline__ float to_tf32(float v) { uint32_t r; asm("cvt.rna.tf32.f32 %0, %1;" : "=r"(r) : "f"(v)); return __uint_as_float(r); }
__device__ __forceinline__ float lds_bf(uint32_t addr) { uint16_t v; asm volatile("ld.shared.u16 %0, [%1];" : "=h"(v) : "r"(addr)); return __uint_as_float((uint32_t)v << 16); }
template <bool RAW>
__device__ __forceinline__ uint4 fold_chunk(uint32_t base, uint32_t tab) {
  const int4 t0 = lds128(tab), t1 = lds128(tab + 16);
  const uint32_t t[8] = {uint32_t(t0.x), uint32_t(t0.y), uint32_t(t0.z), uint32_t(t0.w), uint32_t(t1.x), uint32_t(t1.y), uint32_t(t1.z), uint32_t(t1.w)};
  float w[16];
#pragma unroll
  for (int k = 0; k < 16; k++) {
    const uint32_t a = base + (k & 1 ? t[k >> 1] >> 16 : t[k >> 1] & 0xffff);
    w[k] = RAW ? lds_bf(a) : __int_as_float(lds32(a));
  }
  uint32_t v[4];
#pragma unroll
  for (int c = 0; c < 4; c++) {
    __nv_bfloat162 pk = __floats2bfloat162_rn(w[4 * c] + w[4 * c + 1], w[4 * c + 2] + w[4 * c + 3]);
    v[c] = *reinterpret_cast<uint32_t*>(&pk);
  }
  return make_uint4(v[0], v[1], v[2], v[3]);
}
__device__ __forceinline__ int cw_chunk(int u, int n) {
  return ((u < 44 ? (u >> 1) * 1792 : CW_MAIN + ((u - 44) >> 1) * 1024) + (n >> 3) * 256 + (u & 1) * 128 + (n & 7) * 16) >> 4;
}
__device__ __forceinline__ float log2_sigma(uint32_t v, int n) {
  return __reduce_add_sync(0xffffffffu, (v & 0x7fff) + ((v >> 16) & 0x7fff)) * (1.f / (128 * n)) - 126.02f;
}
__device__ __forceinline__ uint32_t acc_offset(float lg, float cap) { return __float2int_rd(fminf(fmaxf(lg + 131.5f, 0.f), cap + 127.f)) << 7 | 0x2b; }
template <typename F>
__device__ __forceinline__ void fold_weights(F keep, int warp, uint32_t sb, int e, const __nv_bfloat16* __restrict__ wco,
                                             const __nv_bfloat16* __restrict__ ws, const __nv_bfloat16* __restrict__ table, const GPtr gp) {
  const int tid = threadIdx.x, lane = tid & 31;
  const uint32_t bars = sb + OFF_BAR;
  const uint32_t wc16 = ldg16(wco + (lane < NF ? 52 + lane : 0));
  sched_fence();
  const int i0 = fold_i0(e), ni = fold_i0(e + 1) - i0, i = i0 + warp;
  const bool own = warp < ni;
  const uint32_t wb16 = ldg16(wco + (lane < NF ? 26 + lane : 0)), wa16 = ldg16(wco + (lane < NF ? lane : 0));
  const uint32_t sx = ldg32(table + lane * 8), s2 = ldg32(ws + 17576 + lane * 8), s3 = ldg32(ws + 2 * 17576 + lane * 8);
  asm volatile("barrier.cluster.arrive.relaxed.aligned;" ::: "memory");
  bar_sync<7, 288>();
  keep();
  const int ii = lane & 7, ic = i0 + ii;
  auto a_round = [&](int k) {
    const uint4 v = fold_chunk<true>(sb + XOFF_W1 + (ii < ni ? ii * 1392 + (ic & 1) * 8 : 0), sb + XOFF_TAB + 1536 + k * 128 + (lane >> 3) * 32);
    if (ii < ni && (k < 11 || ic >= 24)) gp.s->cw[cw_chunk(lane >> 3, ic < 24 ? 32 + ic : 2 * ic - 23) + k * 224 - (k == 11 ? (lane >> 4) * 48 : 0)] = v;
  };
  if (warp >= 6) {
    if (tid < 192 + 7) asm volatile("st.shared.v4.b32 [%0], {%1, %1, %1, %1};" ::"r"(sb + XOFF_W1 + (tid - 192) * 1392 + 1360), "r"(0) : "memory");
    sts64f(sb + XOFF_M + 26 * 160 + (tid - 192) * 8, 0.f, 0.f);
    if (tid < 256 - 8) sts64f(sb + XOFF_M + 26 * 160 + (tid - 128) * 8, 0.f, 0.f);
    if (tid < 192 + 48) gp.s->cw[cw_chunk(tid - 192, 28 + e)] = make_uint4(0, 0, 0, 0);
    if (tid < 192 + NF) {
      sts64f(sb + XOFF_M + lane * 160 + 104, bf_lo(wb16), 0.f);
      sts64f(sb + XOFF_M + lane * 160 + 112, 0.f, 0.f);
      sts64f(sb + XOFF_M + lane * 160 + 120, 0.f, 0.f);
    }
    if (warp == 7) {
      const float lx = log2_sigma(sx, 64) + 4.7f, l1 = log2_sigma(lane < NF ? wa16 : 0, NF), l2 = log2_sigma(lane < NF ? wb16 : 0, NF);
      const float l3 = log2_sigma(lane < NF ? wc16 : 0, NF) + log2_sigma(s3, 64) + lx;
      const float ct = bf_lo(acc_offset(fmaxf(l1, fmaxf(l2, l3) + log2_sigma(s2, 64) + lx), 100.f));
      const float w1i = __shfl_sync(0xffffffffu, bf_lo(wa16), ic);
      if (lane < 16 && ii < ni) sts64f(sb + XOFF_S + ii * 3152 + (26 + (lane >> 3)) * 112 + 104, lane < 8 ? ct : w1i, lane < 8 ? -ct : 0.f);
    }
    bar_sync<5, 64>();
    mbar_wait(bars + 8 * BAR_W0, 0);
    if (warp == 7) bar_arrive<4, 256>();
#pragma unroll 1
    for (int k = warp == 6 ? 0 : AR; k < (warp == 6 ? AR : 12); k++) a_round(k);
  } else {
    const uint32_t a = sb + XOFF_W3 + (tid < 169 ? tid : 0) * 8;
    const int o = tid * 2, o2 = o + 1;
    const uint32_t mo = sb + XOFF_M + (o / 13) * 160 + (o % 13) * 8, mo2 = sb + XOFF_M + (o2 / 13) * 160 + (o2 % 13) * 8;
    mbar_wait(bars + 8 * BAR_GIDX, 0);
    float m0 = 0.f, m1 = 0.f, m2 = 0.f, m3 = 0.f;
#pragma unroll 1
    for (int g0 = 0; g0 < NF; g0 += MU) {
      int2 v[MU];
      float w[MU];
#pragma unroll
      for (int g = 0; g < MU; g++) { v[g] = lds64(a + (g0 + g) * 1352); w[g] = __shfl_sync(0xffffffffu, bf_lo(wc16), g0 + g); }
#pragma unroll
      for (int g = 0; g < MU; g++) {
        m0 = fmaf(w[g], bf_lo(v[g].x), m0); m1 = fmaf(w[g], bf_hi(v[g].x), m1);
        m2 = fmaf(w[g], bf_lo(v[g].y), m2); m3 = fmaf(w[g], bf_hi(v[g].y), m3);
      }
    }
    if (tid < 169) {
      sts64f(mo, to_tf32(m0), to_tf32(m1));
      sts64f(mo2, to_tf32(m2), to_tf32(m3));
    }
  }
  if (warp < 7) {
  const uint32_t sT = sb + XOFF_S + (own ? warp : 0) * 3152;
  const int g = lane >> 2, c = lane & 3;
  uint32_t af[2][8];
  mbar_wait(bars + 8 * BAR_FULL, 0);
#pragma unroll
  for (int k = 0; k < 8; k++) {
    const int h = 4 * k + c;
    const uint32_t a = sb + XOFF_W2 + ((h < NF ? h : 0) * 676 + (own ? i : 0) * 26 + 2 * g) * 2;
    af[0][k] = lds32(a);
    af[1][k] = lds32(a + (g < 5 ? 32 : 0));
  }
  bar_sync<4, 256>();
  if (own) {
    float d[4][2][4] = {};
#pragma unroll
    for (int ks = 0; ks < 4; ks++) {
#pragma unroll
      for (int n = 0; n < 4; n++) {
        const uint32_t b0 = lds32(sb + XOFF_M + (8 * ks + c) * 160 + (8 * n + g) * 4);
        const uint32_t b1 = lds32(sb + XOFF_M + (8 * ks + c + 4) * 160 + (8 * n + g) * 4);
#pragma unroll
        for (int m = 0; m < 2; m++)
          asm("mma.sync.aligned.m16n8k8.row.col.f32.tf32.tf32.f32 {%0,%1,%2,%3}, {%4,%5,%6,%7}, {%8,%9}, {%0,%1,%2,%3};"
              : "+f"(d[n][m][0]), "+f"(d[n][m][1]), "+f"(d[n][m][2]), "+f"(d[n][m][3])
              : "r"(af[m][2 * ks] << 16), "r"(af[m][2 * ks] & 0xffff0000u), "r"(af[m][2 * ks + 1] << 16),
                "r"(af[m][2 * ks + 1] & 0xffff0000u), "r"(b0), "r"(b1));
      }
    }
#pragma unroll
    for (int n = 0; n < 4; n++) {
      if (n < 3 || c < 2) {
        const uint32_t a = sT + 2 * g * 112 + (8 * n + 2 * c) * 4;
        sts64f(a, d[n][0][0], d[n][0][1]);
        sts64f(a + 112, d[n][0][2], d[n][0][3]);
        if (g < 5) {
          sts64f(a + 16 * 112, d[n][1][0], d[n][1][1]);
          sts64f(a + 17 * 112, d[n][1][2], d[n][1][3]);
        }
      }
    }
  }
  bar_sync<5, 224>();
#pragma unroll 1
  for (int k = warp; k < 12; k += 7) {
    const uint4 v = fold_chunk<false>(sb + XOFF_S + (ii < ni ? ii : 0) * 3152, sb + XOFF_TAB + k * 128 + (lane >> 3) * 32);
    if (ii < ni) gp.s->cw[cw_chunk(lane >> 3, ic < 24 ? ic : 2 * ic - 24) + k * 224 - (k == 11 ? (lane >> 4) * 48 : 0)] = v;
  }
  }
  __syncwarp();
  if (lane == 0) flag_add(&gp.s->foldflag);
  asm volatile("barrier.cluster.wait.acquire.aligned;" ::: "memory");
  bar_sync<4, 256>();
  mbar_wait(bars + 8 * BAR_GDONE, 0);
  if (tid >= 128 && tid < 132) mbar_arrive(ev_bar(bars, EV_END));
}

__global__ void __cluster_dims__(2, 1, 1) __launch_bounds__(384, 1)
xdeepfm_kernel(const int* __restrict__ idx, const __nv_bfloat16* __restrict__ table, const __nv_bfloat16* __restrict__ w1,
               const __nv_bfloat16* __restrict__ b1, const __nv_bfloat16* __restrict__ w2,
               const __nv_bfloat16* __restrict__ ws, const __nv_bfloat16* __restrict__ wco,
               const __nv_bfloat16* __restrict__ bout, __nv_bfloat16* __restrict__ out, const GPtr gp,
               const __grid_constant__ CUtensorMap tmW, const __grid_constant__ CUtensorMap tmT) {
  int myidx, idx1, idx2 = 0, idx3 = 0;
  {
    const int t = threadIdx.x, b = blockIdx.x, half = (b >> 1) ^ (t >= 256 ? t >> 4 : 0);
    const int* ip = idx + (((b >> 3) & 15) * 256 + (half & 1) * 128 + (t < 256 ? min(min(t >> 5, 4) * 4 + (t >> 5) * 16 + min(t & 31, 19), 127) : (b & 1) * 64 + ((t >> 1) & 48) + (t & 15))) * NF;
    asm volatile("{\n.reg .pred p;\nsetp.ge.u32 p, %5, 256;\nld.global.nc.v2.s32 {%0, %1}, [%4];\n@p ld.global.nc.v2.s32 {%2, %3}, [%4 + 8];\n}"
                 : "=r"(myidx), "=r"(idx1), "+r"(idx2), "+r"(idx3) : "l"(ip), "r"(t));
  }
  extern __shared__ __align__(1024) uint8_t smem[];
  const uint32_t sb = (uint32_t)__cvta_generic_to_shared(smem);
  const uint32_t bars = sb + OFF_BAR;
  const int tid = threadIdx.x, lane = tid & 31;
  const int warp = __shfl_sync(0xffffffffu, tid >> 5, 0);
  const int cta = blockIdx.x;
  const bool gemm = cta < NGEMM;
  const int nt = cta & 7, rank = cta & 1;

  uint32_t sx, sw;
  uint4 bv;
  asm volatile("{\n.reg .pred p;\nsetp.eq.u32 p, %9, 7;\n@p ld.global.nc.u32 %0, [%6];\n@p ld.global.nc.u32 %1, [%7];\n@p ld.global.nc.v4.u32 {%2, %3, %4, %5}, [%8];\n}"
               : "=r"(sx), "=r"(sw), "=r"(bv.x), "=r"(bv.y), "=r"(bv.z), "=r"(bv.w)
               : "l"(table + cta * 256 + lane * 8), "l"(w1 + nt * 192 + lane * 2),
                 "l"(b1 + (lane < 24 ? nt * 192 : 1536 - 192 + (nt >> 2) * 64) + lane * 8), "r"(tid >> 5));
  auto keep = [&]() {
    asm volatile("{\n.reg .pred p;\nsetp.ne.u32 p, %0, 0;\n@p st.shared.v2.b32 [%0], {%1, %2};\n@p st.shared.v2.b32 [%0 + 8], {%3, %4};\n"
                 "@p st.shared.b32 [%0 + 16], %5;\n@p st.shared.b32 [%0 + 24], %6;\n@p st.shared.v4.b32 [%0 + 32], {%7, %8, %9, %10};\n}"
                 ::"r"((uint32_t)(size_t)table & 1), "r"(myidx), "r"(idx1), "r"(idx2), "r"(idx3), "r"(sx), "r"(sw), "r"(bv.x), "r"(bv.y), "r"(bv.z), "r"(bv.w) : "memory");
  };
  if (warp == 8 && elect1()) {
    mbar_init(bars + 8 * BAR_GIDX, 1);
    mbar_init(bars + 8 * BAR_FULL, 1);
    mbar_init(bars + 8 * BAR_W0, 1);
    asm volatile("fence.mbarrier_init.release.cluster;" ::: "memory");
    if (gemm) {
      mbar_expect_tx(bars + 8 * BAR_W0, 4 * UNIT);
#pragma unroll
      for (int i = 0; i < 4; i++)
        tma_load(sb + (U_W + i) * UNIT, &tmW, i < 3 ? nt * 192 + i * 64 : 1536 + (nt >> 2) * 64, 0, bars + 8 * BAR_W0);
    } else {
      mbar_expect_tx(bars + 8 * BAR_GIDX, 35152);
      bulk_load(sb + XOFF_W3, ws + 2 * 17576, 35152, bars + 8 * BAR_GIDX);
    }
  }
  if (warp == 8 && !gemm) bar_arrive<7, 288>();
  if (threadIdx.x < 256) {}
  else if (threadIdx.x >= 384 - 16) {
    const int l = threadIdx.x & 7;
    if (l < 7) asm volatile("prefetch.global.L2 [%0];" ::"l"(w1 + (((cta >> 3 & 15) * 2 + (cta & 1)) * 2 + ((threadIdx.x >> 3) & 1)) * DIN + (l < 6 ? (cta & 6) * 192 + l * 64 : 1536 + (cta & 4) * 16)));
  }
  else if (threadIdx.x >= 352 && threadIdx.x < 359) {
    const int l = blockIdx.x * 7 + threadIdx.x - 352;
    if (l < 824) asm volatile("prefetch.global.L2 [%0];" ::"l"(ws + (823 - l) * 64));
  }

  if (warp >= 8) {
    const int pw = warp - 8;
    const bool lead = elect1();
    if (lead) {
      if (pw) mbar_init(bars + 8 * (pw < 3 ? BAR_FULL + pw : BAR_CIDX), 1);
      else mbar_init(bars + 8 * BAR_GDONE, 4);
      asm volatile("fence.mbarrier_init.release.cluster;" ::: "memory");
    }
    __syncwarp();
    asm volatile("barrier.cluster.arrive.relaxed.aligned;" ::: "memory");
    if (lead) {
      if (gemm) w_prefetch(w1, 1, cta, pw);
      if (pw == 0) {
        if (gemm) {
          mbar_expect_tx(bars + 8 * BAR_FULL, 2 * UNIT);
          asm volatile("prefetch.tensormap [%0];" ::"l"(&tmT) : "memory");
        } else {
          const int i0 = fold_i0(cta - NGEMM), ni = fold_i0(cta - NGEMM + 1) - i0;
          mbar_expect_tx(bars + 8 * BAR_W0, ni * 1360 + sizeof(SlotTab));
#pragma unroll 1
          for (int i = 0; i < ni; i++) bulk_load(sb + XOFF_W1 + i * 1392, ws + (((i0 + i) * 676) & ~7), 1360, bars + 8 * BAR_W0);
          bulk_load(sb + XOFF_TAB, gp.tab, sizeof(SlotTab), bars + 8 * BAR_W0);
          mbar_expect_tx(bars + 8 * BAR_FULL, 35152);
          bulk_load(sb + XOFF_W2, ws + 17576, 35152, bars + 8 * BAR_FULL);
        }
      } else if (pw == 3 && !gemm) {
        mbar_expect_tx(bars + 8 * BAR_CIDX, NC_EXTRA * (NF * 4 + sizeof(Job)));
        bulk_load(sb + XOFF_CIDX, idx + cin_start(cta) * NF, NC_EXTRA * NF * 4, bars + 8 * BAR_CIDX);
        bulk_load(sb + XOFF_JOB, gp.jobs + (32 + rank * (32 + NC_EXTRA)) * sizeof(Job) / 16, NC_EXTRA * sizeof(Job), bars + 8 * BAR_CIDX);
      }
    }
    __syncwarp();
    asm volatile("setmaxnreg.dec.sync.aligned.u32 24;");
    if (elect1()) {
      mbar_init(bars + 8 * (BAR_EV + pw), 4);
      mbar_init(bars + 8 * (BAR_EV + 4 + pw), 4);
      mbar_init(bars + 8 * (BAR_FULL + 4 + pw), 1);
      mbar_init(bars + 8 * (pw == 2 ? BAR_CW : BAR_DNN + pw), pw == 2 ? 1 : 1 << pw);
      if (pw == 0) mbar_init(bars + 8 * (BAR_FULL + 3), 1);
#pragma unroll
      for (int i = 0; i < 8; i++)
        mbar_init(bars + 8 * (BAR_CFULL + pw * 8 + i), (!gemm && (pw & 1)) ? 4 : i == 4 && pw == 3 ? NR : 1);
      if (pw < 3) mbar_init(bars + 8 * (pw < 2 ? BAR_C0 + pw : BAR_WIN), 1);
      asm volatile("fence.mbarrier_init.release.cluster;" ::: "memory");
    }
    __syncwarp();
    bar_sync<6, 128>();
    asm volatile("barrier.cluster.wait.acquire.aligned;" ::: "memory");
    if (!gemm && elect1()) mbar_arrive(bars + 8 * BAR_GDONE);
    __syncwarp();
    if (gemm) {
      {
        const uint32_t a = sb + OFF_GIDX + ((lane >> 4) * 64 + pw * 16 + (lane & 15)) * NF * 4;
        asm volatile("st.shared.v2.b32 [%0], {%1, %2};\nst.shared.v2.b32 [%0 + 8], {%3, %4};"
                     ::"r"(a), "r"(myidx), "r"(idx1), "r"(idx2), "r"(idx3) : "memory");
        keep();
        __syncwarp();
      }
      if (elect1()) {
#pragma unroll
        for (int j = 0; j < 16; j += 8) {
          int r[8];
#pragma unroll
          for (int i = 0; i < 8; i++) r[i] = lds32(sb + OFF_GIDX + ((64 + pw * 16 + j + i) * NF) * 4);
#pragma unroll
          for (int i = 0; i < 8; i++) tma_row_mc(sb + U_XB * UNIT + (rank * 64 + pw * 16 + j + i) * 128, &tmT, r[i], bars + 8 * BAR_FULL);
        }
        int s = 1;
#pragma unroll 1
        for (int fi = 1; fi < NF; fi++) {
          const int f = fresh(fi), pw = fresh(warp) - 8, ct = fresh(cta), nt = ct & 7;
          const int t = f - FS, st = t < 0 ? s : (t & 3) ^ ((t >> 1) & 1), e = f - 3 - (t > 1);
          const uint32_t fb = bars + 8 * (BAR_FULL + (f & 7)), ia = sb + OFF_GIDX + (pw * 16 * NF + f) * 4;
          const uint32_t d = sb + (st == 3 ? U_SP : 2 * st) * UNIT + ((ct & 1) * 64 + pw * 16) * 128;
          if (f == 4) mbar_wait(bars + 8 * BAR_GIDX, 0);
          int r[2][RB];
#pragma unroll
          for (int i = 0; i < RB; i++) r[0][i] = lds32(ia + i * NF * 4);
          if (e >= 0) mbar_wait(ev_bar(bars, e), ev_par(e));
          if (pw == 0) mbar_expect_tx(fb, t < 0 ? 8 * UNIT : 6 * UNIT);
#pragma unroll
          for (int j = 0; j < 16 / RB; j++) {
#pragma unroll
            for (int i = 0; i < RB; i++) r[(j + 1) & 1][i] = lds32(ia + (RB * j + RB + i + (RB * j + RB >= 16) * 48) * NF * 4);
#pragma unroll
            for (int i = 0; i < RB; i++) tma_row_mc(d + (RB * j + i) * 128, &tmT, r[j & 1][i], fb);
          }
          if (t < 0) {
#pragma unroll
            for (int j = 0; j < 16 / RB; j++) {
              if (j + 1 < 16 / RB) {
#pragma unroll
                for (int i = 0; i < RB; i++) r[(j + 1) & 1][i] = lds32(ia + (64 + RB * j + RB + i) * NF * 4);
              }
#pragma unroll
              for (int i = 0; i < RB; i++) tma_row_mc(d + U_XB * UNIT + (RB * j + i) * 128, &tmT, r[j & 1][i], fb);
            }
          }
          tma_load(sb + (U_W + 4 * st + pw) * UNIT, &tmW, pw < 3 ? nt * 192 + pw * 64 : 1536 + (nt >> 2) * 64, f * 64, fb);
          if (f == GI && pw < 2) {
            if (pw == 0) mbar_expect_tx(bars + 8 * BAR_GIDX, 128 * NF * 4);
            bulk_load(sb + OFF_GIDX + pw * 64 * NF * 4, idx + ((ct >> 3) * 256 + (((ct >> 1) ^ pw) & 1) * 128 + (ct & 1) * 64) * NF, 64 * NF * 4, bars + 8 * BAR_GIDX);
          }
          if (f == GI && pw == 2) {
            mbar_expect_tx(bars + 8 * BAR_CIDX, 32 * (NF * 4 + sizeof(Job)));
            bulk_load(sb + OFF_CIDX, idx + (ct * NC_GEMM & ~1) * NF, 30 * NF * 4, bars + 8 * BAR_CIDX);
            bulk_load(sb + OFF_PIDX, idx + (POOL + (group_of(ct) * NR & ~1)) * NF, 2 * NF * 4, bars + 8 * BAR_CIDX);
            bulk_load(sb + OFF_JOB, gp.jobs + (ct & 1) * ((32 + NC_EXTRA) * sizeof(Job) / 16), 32 * sizeof(Job), bars + 8 * BAR_CIDX);
          }
          if (f + WD < NF) w_prefetch(w1, f + WD, ct, pw);
          if (++s == 3) s = 0;
        }
        mbar_wait(bars + 8 * BAR_T, 0);
#pragma unroll 1
        for (int ti = 0; ti < 8; ti++) {
          const int t = fresh(ti), pw = fresh(warp) - 8, e = t < 4 ? 22 - !t : 19 + t;
          const uint32_t ia = sb + OFF_TIDX + t * 256 + pw * 64, fb = bars + 8 * (BAR_FULL + ((NF + t) & 7));
          const uint32_t d = sb + b_x(t) * UNIT + ((fresh(cta) & 1) * 64 + pw * 16) * 128;
          int4 r[2];
          r[0] = lds128(ia);
          r[1] = lds128(ia + 16);
          mbar_wait(ev_bar(bars, e), ev_par(e));
          if (pw == 0) mbar_expect_tx(fb, t < 3 ? 2 * UNIT : 5 * UNIT);
#pragma unroll
          for (int j = 0; j < 4; j++) {
            tma_row_mc(d + (4 * j + 0) * 128, &tmT, r[j & 1].x, fb);
            tma_row_mc(d + (4 * j + 1) * 128, &tmT, r[j & 1].y, fb);
            tma_row_mc(d + (4 * j + 2) * 128, &tmT, r[j & 1].z, fb);
            tma_row_mc(d + (4 * j + 3) * 128, &tmT, r[j & 1].w, fb);
            if (j < 2) r[j & 1] = lds128(ia + 32 + 16 * j);
          }
        }
        mbar_arrive(bars + 8 * BAR_GDONE);
      }
      __syncwarp();
    }
    {
    int cta; asm volatile("mov.u32 %0, %%ctaid.x;" : "=r"(cta));
    cta = __shfl_sync(0xffffffffu, cta, 0);
    const bool gemm = cta < NGEMM;
    const int bt = cta >> 3, nt = cta & 7;
    if (pw == 3) {
      if (elect1()) {
        if (!gemm) flag_wait(&gp.s->foldflag, (gp.s->epoch[fresh(cta)] + 1) * NEXTRA * 8, 0);
        asm volatile("fence.proxy.async.global;" ::: "memory");
        if (gemm) mbar_wait(ev_bar(bars, EV_CW), ev_par(EV_CW));
        mbar_expect_tx(bars + 8 * BAR_CW, CW_BYTES);
        bulk_load(sb + OFF_CW, gp.s->cw, CW_CUT * 1792, bars + 8 * BAR_CW);
        bulk_load(sb + OFF_CW2, gp.s->cw + CW_CUT * 1792 / 16, (22 - CW_CUT) * 1792, bars + 8 * BAR_CW);
        bulk_load(sb + OFF_CWL, gp.s->cw + CW_MAIN / 16, CW_LIN, bars + 8 * BAR_CW);
      }
      __syncwarp();
    }
    if (pw < NLW || !gemm) {
      if (elect1()) {
        const bool gemm = blockIdx.x < NGEMM;
        mbar_wait(bars + 8 * BAR_GDONE, 0);
        mbar_wait(bars + 8 * BAR_CIDX, 0);
#pragma unroll 1
        for (uint32_t o = sb + (gemm ? OFF_JOB : XOFF_JOB) + (warp - 8) * sizeof(Job); o;) {
          const int2 j0 = lds64(o), j1 = lds64(o + 8), j2 = lds64(o + 16);
          const uint32_t d = j1.x, cb = j1.y, ia = j2.x;
          o = j2.y;
          mbar_wait(j0.x, j0.y);
          mbar_expect_tx(cb, NF * 128);
#pragma unroll
          for (int k = 0; k < NF; k += 2 * LB) {
            int2 r[LB];
#pragma unroll
            for (int i = 0; i < LB; i++) if (k + 2 * i < NF) r[i] = lds64(ia + (k + 2 * i) * 4);
#pragma unroll
            for (int i = 0; i < LB; i++) if (k + 2 * i < NF) {
              tma_row(d + (k + 2 * i) * 128, &tmT, r[i].x, cb);
              tma_row(d + (k + 2 * i + 1) * 128, &tmT, r[i].y, cb);
            }
          }
        }
        if (gemm) mbar_wait(bars + 8 * BAR_POOL, 0);
      }
      __syncwarp();
    }
    if (pw == 3) {
      unsigned epoch;
      asm volatile("ld.global.u32 %0, [%1];" : "=r"(epoch) : "l"(gp.s->epoch + fresh(cta)));
      epoch++;
      const float bo = sb == SMEM_BASE + ((cta & 1) << 24) ? bf2f(bout[0]) : __int_as_float(0x7fc00000);
      if (gemm) {
        mbar_wait(bars + 8 * BAR_PART, 0);
        float4* dst = reinterpret_cast<float4*>(gp.s->part + nt * NB + bt * 256);
        dst[lane] = lds128f(sb + OFF_PART + lane * 16);
        dst[lane + 32] = lds128f(sb + OFF_PART + 512 + lane * 16);
        __syncwarp();
        if (lane == 0) flag_add(gp.s->dflag + (fresh(cta) >> 3) * 8);
      }
      const int c0 = cin_start(cta), ncin = gemm ? NC_GEMM : NC_EXTRA;
      flag_wait(gp.s->dflag + ((lane == 0 ? c0 : lane == 1 ? POOL : c0 + ncin - 1) >> 8) * 8, epoch * 8, 200);
      __syncwarp();
#pragma unroll 1
      for (int r = lane; r < ncin + gemm; r += 32) {
        const int b = r < ncin ? c0 + r : POOL + group_of(cta) * NR + (lds32(sb + OFF_WIN) & (NR - 1));
        float s = bo;
#pragma unroll
        for (int n = 0; n < 8; n++) s += __ldcg(gp.s->part + n * NB + b);
        sts64f(sb + (gemm ? OFF_DNN : XOFF_DNN) + r * 8, 0.125f * s, __int_as_float(b));
      }
      __syncwarp();
      if (lane == 0) { mbar_arrive(bars + 8 * BAR_DNN); gp.s->epoch[fresh(cta)] = epoch; }
    }
    }
  } else {
    const int wg = warp >> 2;
    const int p = tid & 127;
    if (gemm) {
      asm volatile("barrier.cluster.arrive.relaxed.aligned;" ::: "memory");
      if (warp == 7) {
        asm volatile("st.shared.b32 [%0], %1;" ::"r"(sb + OFF_INIT + 4608 + lane * 4), "r"(0x3f003f00) : "memory");
        const int lg = __reduce_add_sync(0xffffffffu, (sx & 0x7fff) + ((sx >> 16) & 0x7fff) + (sw & 0x7fff) + ((sw >> 16) & 0x7fff));
        const uint32_t co = (min(max((lg >> 6) - int((127 - 11.8 - OB) * 128), 0), (130 + OB) * 128) & 0x7f80) | 0x2b;
        const uint32_t bw[4] = {bv.x, bv.y, bv.z, bv.w};
#pragma unroll
        for (int i = 0; i < 8; i++)
          asm volatile("st.shared.v4.b32 [%0], {%1, %2, %2, %2};" ::"r"(sb + OFF_INIT + lane * 144 + i * 16), "r"(__byte_perm(bw[i >> 1], co, i & 1 ? 0x5432 : 0x5410)), "r"(0) : "memory");
        sts32f(sb + OFF_EPI + 1024, -ALPHA * __uint_as_float((co << 16) - 39));
        asm volatile("fence.proxy.async.shared::cta;" ::: "memory");
        bar_arrive<5, 160>();
      } else {
        const int row = min(warp, 4) * 4 + warp * 16 + (lane >> 3);
        const uint32_t a = sb + row * 128 + (((lane ^ row) & 7) << 4);
        const __nv_bfloat16* src = table + (lane & 7) * 8;
        const int l0 = ((fresh(a) >> 7) & 3) | (fresh((int)(size_t)src) & 1);
#pragma unroll
        for (int i = 0; i < 5; i++)
          asm volatile("{\n.reg .pred p;\n.reg .b32 r;\n.reg .b64 a;\nsetp.ne.b32 p, %4, 0;\nshfl.sync.idx.b32 r, %2, %3, 31, 0xffffffff;\n"
                       "mad.wide.s32 a, r, 128, %1;\n@p cp.async.cg.shared.global [%0], [a], 16;\n}"
                       ::"r"((a ^ (i & 1) * 64) + i * 512), "l"(src), "r"(myidx), "r"(4 * i + l0), "r"(int(i < 4 || warp < 4)) : "memory");
      }
      keep();
      asm volatile("barrier.cluster.wait.acquire.aligned;" ::: "memory");
    } else {
      fold_weights(keep, warp, sb, cta - NGEMM, wco, ws, table, gp);
    }
    asm volatile("setmaxnreg.inc.sync.aligned.u32 224;");
    float r0 = 0.f, r1 = 0.f, r2 = 0.f, r3 = 0.f;
    float d1[96];
    Gelu<24> g1;
    unsigned place = NR;
    const uint32_t ep = sb + OFF_EPI + (lane & 3) * 16;
    auto load_w = [&](int t) {
      const int w = warp & 3;
      if (w < 3 && elect1())
        tma_load(sb + (b_w(t) + b_ws(t) * w) * UNIT, &tmW, nt * 192 + w * 64, (NF - 1 - t) * 64, bars + 8 * (BAR_FULL + ((NF + t) & 7)));
    };
    int role; asm volatile("mov.u32 %0, %%ctaid.x;" : "=r"(role));
    role = role < NGEMM ? wg : 2;
    if (fresh(role) == 0) {
      asm volatile("setmaxnreg.inc.sync.aligned.u32 256;");
      float d0[96], dx[32], dw[96];
      Gelu<24> g0;
      bar_sync<5, 160>();
      wg_fence();
      wgmma_ss_n256<0>(dw, dx, ONES_DESC, INIT_DESC, 0);
      wgmma_ss_n192<0>(d0, ONES_DESC, INIT_DESC, 0);
      wg_commit();
      mbar_wait(bars + 8 * BAR_W0, 0);
      asm volatile("cp.async.wait_all;" ::: "memory");
      asm volatile("fence.proxy.async.shared::cta;" ::: "memory");
      bar_sync<2, 256>();
      const uint64_t dA0 = desc_x(rank), dA1 = desc_x(rank ^ 1);
      wg_fence();
#pragma unroll
      for (int k = 0; k < 4; k++) {
        wgmma_ss_n256(dw, dx, dA0 + 2 * k, desc_w(U_W) + 128 * k, 1);
        wgmma_ss_n192(d0, dA1 + 2 * k, desc_w(U_W) + 128 * k, 1);
      }
      wg_commit();
      constexpr unsigned long long STAGES = 0xb4b4924924924ull;
#pragma unroll 1
      for (int f = 1; f < NF - 3; f++) {
        mbar_wait(bars + 8 * (BAR_FULL + (f & 7)), (f >> 3) & 1);
        const int st = (STAGES >> (2 * f)) & 3, xo = (st == 3 ? U_SP : 2 * st) * (UNIT / 16);
        const uint64_t dB = desc_w(U_W + 4 * st);
        wg_fence();
        wgmma_ss_n256(dw, dx, dA0 + xo, dB, 1);
        wgmma_ss_n192(d0, dA1 + xo, dB, 1);
        wg_commit();
        wg_wait<1>();
        if (p < (f > FS ? 4 : 2)) mbar_arrive_cta(ev_bar(bars, f - 1), p & 1);
#pragma unroll
        for (int k = 1; k < 4; k++) {
          wgmma_ss_n256(dw, dx, dA0 + xo + 2 * k, dB + 128 * k, 1);
          wgmma_ss_n192(d0, dA1 + xo + 2 * k, dB + 128 * k, 1);
        }
        wg_commit();
      }
      {
        constexpr int x3 = 2 * (UNIT / 16), x4 = U_SP * (UNIT / 16), x5 = 4 * (UNIT / 16);
        const uint64_t dB3 = desc_w(U_W + 4), dB4 = desc_w(U_W + 12), dB5 = desc_w(U_W + 8);
        mbar_wait(bars + 8 * (BAR_FULL + 7), 0);
        tile_step(d0, dA1 + x3, dB3);
        wg_wait<1>();
        if (p < 4) mbar_arrive_cta(ev_bar(bars, NF - 4), p & 1);
        mbar_wait(bars + 8 * (BAR_FULL + 0), 1);
        tile_step(d0, dA1 + x4, dB4);
        if (WK) wide_step<0, WK>(dw, dx, dA0 + x3, dB3);
        mbar_wait(bars + 8 * (BAR_FULL + 1), 1);
        tile_step(d0, dA1 + x5, dB5);
        wide_step<WK, 4>(dw, dx, dA0 + x3, dB3);
        mbar_wait(bars + 8 * BAR_T, 0);
        g0.start(ep, sb);
        wg_wait<1>();
        wide_step(dw, dx, dA0 + x4, dB4);
        g0.part<0, PE1>(d0, r0, r1);
        wg_wait<1>();
        if (p < 4) mbar_arrive_cta(ev_bar(bars, NF - 3), p & 1);
        wide_step<0, HK>(dw, dx, dA0 + x5, dB5);
        g0.part<PE1, PE2>(d0, r0, r1);
        wg_wait<1>();
        bar_arrive<4, 256>();
        if (p < 4) mbar_arrive_cta(ev_bar(bars, NF - 2), p & 1);
        wide_step<HK, 4>(dw, dx, dA0 + x5, dB5);
        g0.part<PE2, PE0>(d0, r0, r1);
        wg_wait<0>();
        load_w(3);
        if (p < 4) mbar_arrive_cta(ev_bar(bars, NF - 1), p & 1);
      }
      g0.part<PE0, g0.END>(d0, r0, r1);
      Gelu<8> gx;
      gx.start(ep + 12 * 64, sb);
      gx.part<0, gx.END>(dx, r2, r3);
      hand_on(d1, dw);
      g1.take(g0);
      asm volatile("setmaxnreg.dec.sync.aligned.u32 224;");
    }
    if (fresh(role) == 1) {
      float d0[96], dw[96];
      bar_sync<3, 128>();
      wg_fence();
      wgmma_ss_n192<0>(d0, ONES_DESC, INIT_DESC, 0);
      wgmma_ss_n192<0>(dw, ONES_DESC + ((size_t)table & 1), INIT_DESC, 0);
      wg_commit();
      asm volatile("cp.async.wait_all;" ::: "memory");
      asm volatile("fence.proxy.async.shared::cta;" ::: "memory");
      bar_arrive<2, 256>();
      mbar_wait(bars + 8 * BAR_W0, 0);
      mbar_wait(bars + 8 * BAR_FULL, 0);
      wg_fence();
#pragma unroll
      for (int k = 0; k < 4; k++) {
        wgmma_ss_n192(d0, desc_x(U_XB) + 2 * k, desc_w(U_W) + 128 * k, 1);
        wgmma_ss_n192(dw, desc_x(U_XB + 1) + 2 * k, desc_w(U_W) + 128 * k, 1);
      }
      wg_commit();
      int s = 1;
#pragma unroll 1
      for (int f = 1; f < FS; f++) {
        mbar_wait(bars + 8 * (BAR_FULL + (f & 7)), (f >> 3) & 1);
        const uint64_t dA = desc_x(U_XB + 2 * s), dB = desc_w(U_W + 4 * s);
        wg_fence();
        wgmma_ss_n192(d0, dA, dB, 1);
        wgmma_ss_n192(dw, dA + 512, dB, 1);
        wg_commit();
        wg_wait<1>();
        if (p < 2) mbar_arrive_cta(ev_bar(bars, f - 1), p);
#pragma unroll
        for (int k = 1; k < 4; k++) {
          wgmma_ss_n192(d0, dA + 2 * k, dB + 128 * k, 1);
          wgmma_ss_n192(dw, dA + 512 + 2 * k, dB + 128 * k, 1);
        }
        wg_commit();
        if (++s == 3) s = 0;
      }
      wg_wait<0>();
      if (p < 2) mbar_arrive_cta(ev_bar(bars, FS - 1), p);
      {
        const uint32_t a = sb + OFF_GIDX + 64 * NF * 4;
        const uint32_t ww = ldg32(w2 + 2 * p + (p < 96 ? nt * 192 : 1536 - 192 + (nt >> 2) * 64));
        int v[4];
#pragma unroll
        for (int i = 0; i < 4; i++) v[i] = lds32(a + (((p & 15) * 4 + i) * NF + (NF - 1 - (p >> 4))) * 4);
        bar_sync<3, 128>();
        asm volatile("st.shared.v4.b32 [%0], {%1, %2, %3, %4};" ::"r"(sb + OFF_TIDX + p * 16), "r"(v[0]), "r"(v[1]), "r"(v[2]), "r"(v[3]) : "memory");
        sts64f(sb + OFF_EPI + (p >> 3) * 64 + (p & 3) * 16 + (p & 4) * 2, (0.5f / ALPHA) * bf_lo(ww), (0.5f / ALPHA) * bf_hi(ww));
        bar_sync<3, 128>();
        if (p < 2) {
          flag_wait(&gp.s->foldflag, (gp.s->epoch[cta] + 1) * NEXTRA * 8, 0);
          mbar_arrive(bars + 8 * BAR_T);
        }
        __syncwarp();
      }
      mbar_wait(ev_bar(bars, FS), ev_par(FS));
      unsigned* tp = gp.s->place + group_of(cta) * 8;
      asm volatile("" : "+l"(tp));
      sched_fence();
      mbar_wait(bars + 8 * (BAR_FULL + 2), 1);
      bar_sync<4, 256>();
#pragma unroll
      for (int t = 0; t < 4; t++) {
        if (t) mbar_wait(bars + 8 * (BAR_FULL + 2 + t), 1);
        const uint64_t dA = desc_x(b_x(t)), dB = desc_w(b_w(t), b_ws(t));
        wg_fence();
#pragma unroll
        for (int k = 0; k < 4; k++) {
          wgmma_ss_n192(d0, dA + 2 * k, dB + 128 * k, 1);
          wgmma_ss_n192(dw, dA + 512 + 2 * k, dB + 128 * k, 1);
          if (k == 1 && t) {
            wg_commit();
            wg_wait<1>();
            mbar_wait(ev_bar(bars, NF - 1), ev_par(NF - 1));
            load_w(3 + t);
            if (t == 1 && p < 4) mbar_arrive_cta(ev_bar(bars, 26), p & 1);
            if (t == 3)
              asm volatile("{\n.reg .pred p;\nsetp.eq.u32 p, %2, 0;\n@p st.shared.b32 [%1], %0;\n@p mbarrier.arrive.shared::cta.b64 _, [%3];\n}"
                           ::"r"(place), "r"(sb + OFF_WIN), "r"(p), "r"(bars + 8 * BAR_WIN) : "memory");
            wg_fence();
          }
        }
        wg_commit();
        if (t == 0)
          asm volatile("{\n.reg .pred p;\nsetp.eq.u32 p, %2, 0;\n@p atom.relaxed.gpu.global.inc.u32 %0, [%1], 7;\n}" : "+r"(place) : "l"(tp), "r"(p));
      }
      mbar_wait(bars + 8 * (BAR_FULL + 6), 1);
      tile_step(d0, desc_x(b_x(4)), desc_w(b_w(4)));
      wg_wait<1>();
      load_w(7);
      if (p < 4) mbar_arrive(ev_bar(bars, EV_CW));
      mbar_wait(bars + 8 * (BAR_FULL + 7), 1);
      tile_step(d0, desc_x(b_x(5)), desc_w(b_w(5)));
      mbar_wait(bars + 8 * (BAR_FULL + 0), 0);
      tile_step(d0, desc_x(b_x(6)), desc_w(b_w(6)));
      mbar_wait(bars + 8 * (BAR_FULL + 1), 0);
      tile_step(d0, desc_x(b_x(7)), desc_w(b_w(7), 4));
      tile_step(dw, desc_x(b_x(4) + 1), desc_w(b_w(4)));
      Gelu<24> g0;
      g0.start(ep, sb);
      mbar_wait(bars + 8 * BAR_WIN, 0);
      place = lds32(sb + OFF_WIN);
      wg_wait<1>();
      tile_step(dw, desc_x(b_x(5) + 1), desc_w(b_w(5)));
      g0.part<0, PS>(d0, r0, r1);
      wg_wait<1>();
      if (p < 4) mbar_arrive(ev_bar(bars, 30));
      tile_step(dw, desc_x(b_x(6) + 1), desc_w(b_w(6)));
      g0.part<PS, 2 * PS>(d0, r0, r1);
      wg_wait<1>();
      if (p < 4) mbar_arrive(ev_bar(bars, 31));
      tile_step(dw, desc_x(b_x(7) + 1), desc_w(b_w(7), 4));
      g0.part<2 * PS, 2 * PS + PS2>(d0, r0, r1);
      wg_wait<0>();
      if (p < 4) mbar_arrive(ev_bar(bars, EV_END));
      g0.part<2 * PS + PS2, g0.END>(d0, r0, r1);
      hand_on(d1, dw);
      g1.take(g0);
    }
    g1.ep = ep;
    if (fresh(role) < 2) g1.part<0, g1.END - GK, false>(d1, r2, r3);

    {
    int cta, tid;
    asm volatile("mov.u32 %0, %%ctaid.x;" : "=r"(cta));
    asm volatile("mov.u32 %0, %%tid.x;" : "=r"(tid));
    const bool gemm = role < 2;
    const int lane = tid & 31, p = tid & 127;
    const int rb = !wg ? 0 : gemm ? NC_WG0 : NC_EXTRA / 2;
    place = __shfl_sync(0xffffffffu, place, 0);
    const int nj = !gemm ? NC_EXTRA / 2 : wg ? NC_GEMM - NC_WG0 + (place < NR) : NC_WG0;
    const uint32_t cinb = sb + (gemm ? OFF_CIN + rb * CROW : wg ? XOFF_CIN1 : XOFF_CIN0);
    CinCtx c;
    cin_setup(c, sb, wg, tid, gemm, nj);
    if (place == 1 && NR == 2) c.tab1 += 0x20000;
    c.co = cinb;
    c.cin = p * 4;
    uint32_t ra, on;
    float dn;
    __nv_bfloat16* op;
    auto prepare = [&](int r) {
      on = (p & 7) == 0 && r >= 0;
      r = max(r, 0);
      ra = cinb + (p & 7) * 16 + r * CROW;
      const int2 v = lds64(sb + (gemm ? OFF_DNN : XOFF_DNN) + (rb + r) * 8);
      dn = __int_as_float(v.x);
      op = out + v.y;
      asm volatile("" : "+r"(ra), "+r"(on), "+f"(dn), "+l"(op));
      sched_fence();
    };
    auto result = [&]() {
      const float4 v0 = lds128f(ra), v1 = lds128f(ra + 128), v2 = lds128f(ra + 256), v3 = lds128f(ra + 384);
      float s = ((((v0.x + dn) + v0.y) + (v0.z + v0.w)) + ((v1.x + v1.y) + (v1.z + v1.w))) +
                (((v2.x + v2.y) + (v2.z + v2.w)) + ((v3.x + v3.y) + (v3.z + v3.w)));
      s += __shfl_xor_sync(0xffffffffu, s, 1);
      s += __shfl_xor_sync(0xffffffffu, s, 2);
      s += __shfl_xor_sync(0xffffffffu, s, 4);
      asm volatile("{\n.reg .pred p;\n.reg .b16 v;\nsetp.ne.u32 p, %2, 0;\ncvt.rn.bf16.f32 v, %1;\n@p st.global.b16 [%0], v;\n}" ::"l"(op), "f"(s), "r"(on) : "memory");
    };
    cin_run(c, [&](uint32_t (&x)[11][2]) {
      mbar_wait(bars + 8 * BAR_GDONE, 0);
      mbar_wait(bars + 8 * (BAR_C0 + wg), 0);
      const uint32_t first = sb + (!gemm ? OFF_GIDX + wg * XSLOT : wg ? 24 * UNIT : OFF_GIDX + 2 * XSLOT);
      g1.part<g1.END - GK, g1.END, false>(d1, r2, r3, [&](int i) { cin_ldsm(c, first, x, i); });
#pragma unroll
      for (int i = GK; i < 5; i++) cin_ldsm(c, first, x, i);
      mbar_wait(bars + 8 * BAR_CW, 0);
    }, [&]() {
      sched_fence();
      const bool b0 = lane & 1, b1_ = lane & 2;
      float a = b0 ? r1 : r0, b = b0 ? r0 : r1, cc = b0 ? r3 : r2, d = b0 ? r2 : r3;
      a += __shfl_xor_sync(0xffffffffu, b, 1);
      cc += __shfl_xor_sync(0xffffffffu, d, 1);
      float e = b1_ ? cc : a, f = b1_ ? a : cc;
      e += __shfl_xor_sync(0xffffffffu, f, 2);
      const uint32_t row4 = (tid & 0x1c) | ((tid & 1) << 5) | ((tid & 0x60) << 1) | ((tid & 2) << 7);
      sts32f(sb + OFF_PART + (row4 ^ (((((cta >> 1) ^ wg) & 1) << 9) | ((~cta & ~wg & 1) << 8))), e);
      __syncwarp();
      if (lane == 0) mbar_arrive(bars + 8 * BAR_PART);
      mbar_wait(ev_bar(bars, gemm ? EV_CIN : EV_END), gemm);
    }, [&]() {
      mbar_wait(bars + 8 * BAR_DNN, 0);
      prepare(nj - 16 + (p >> 3));
    });
    asm volatile("bar.sync %0, 128;" ::"r"(1 + 2 * wg) : "memory");
    result();
#pragma unroll 1
    for (int r = nj - 32; r > -16; r -= 16) {
      prepare(r + (p >> 3));
      result();
    }
    }
  }
}

typedef CUresult (*EncodeFn)(CUtensorMap*, CUtensorMapDataType, cuuint32_t, void*, const cuuint64_t*, const cuuint64_t*,
                             const cuuint32_t*, const cuuint32_t*, CUtensorMapInterleave, CUtensorMapSwizzle,
                             CUtensorMapL2promotion, CUtensorMapFloatOOBfill);

extern "C" void kernel_launch(void* const* d_in, const int* in_sizes, int n_in, void* d_out, int out_size) {
  void* fn = nullptr;
  cudaDriverEntryPointQueryResult q;
  cudaGetDriverEntryPoint("cuTensorMapEncodeTiled", &fn, cudaEnableDefault, &q);
  EncodeFn enc = (EncodeFn)fn;
  CUtensorMap tmW, tmT;
  const cuuint32_t es[3] = {1, 1, 1};
  {
    cuuint64_t dims[2] = {DIN, DIN}, st[1] = {DIN * 2};
    cuuint32_t box[2] = {64, 64};
    enc(&tmW, CU_TENSOR_MAP_DATA_TYPE_BFLOAT16, 2, d_in[4], dims, st, box, es, CU_TENSOR_MAP_INTERLEAVE_NONE,
        CU_TENSOR_MAP_SWIZZLE_128B, CU_TENSOR_MAP_L2_PROMOTION_NONE, CU_TENSOR_MAP_FLOAT_OOB_FILL_NONE);
  }
  {
    cuuint64_t dims[2] = {64, (cuuint64_t)(in_sizes[1] / 64)}, st[1] = {128};
    cuuint32_t box[2] = {64, 1};
    enc(&tmT, CU_TENSOR_MAP_DATA_TYPE_BFLOAT16, 2, d_in[1], dims, st, box, es, CU_TENSOR_MAP_INTERLEAVE_NONE,
        CU_TENSOR_MAP_SWIZZLE_128B, CU_TENSOR_MAP_L2_PROMOTION_NONE, CU_TENSOR_MAP_FLOAT_OOB_FILL_NONE);
  }
  GPtr gp;
  gp.zero = 0;
  cudaGetSymbolAddress((void**)&gp.s, g_scratch);
  cudaGetSymbolAddress((void**)&gp.tab, g_slot_tab);
  cudaGetSymbolAddress((void**)&gp.jobs, g_jobs);
  cudaFuncSetAttribute(xdeepfm_kernel, cudaFuncAttributeMaxDynamicSharedMemorySize, SMEM_BYTES);
  xdeepfm_kernel<<<GRID, 384, SMEM_BYTES, cudaStreamPerThread>>>(
      (const int*)d_in[0], (const __nv_bfloat16*)d_in[1], (const __nv_bfloat16*)d_in[4], (const __nv_bfloat16*)d_in[5],
      (const __nv_bfloat16*)d_in[6], (const __nv_bfloat16*)d_in[2], (const __nv_bfloat16*)d_in[3],
      (const __nv_bfloat16*)d_in[7], (__nv_bfloat16*)d_out, gp, tmW, tmT);
}
```

```cpp
#include <cuda_runtime.h>
#include <cuda_bf16.h>
#include <cuda.h>
#include <stdint.h>

template <int TB = 1>
__device__ __forceinline__ void wgmma_ss_n256(float (&d)[96], float (&e)[32], uint64_t descA, uint64_t descB, int scaleD) {
  asm volatile("{\n.reg .pred p;\nsetp.ne.b32 p, %130, 0;\n"
      "wgmma.mma_async.sync.aligned.m64n256k16.f32.bf16.bf16 {"
      "%0, %1, %2, %3, %4, %5, %6, %7, %8, %9, %10, %11, %12, %13, %14, %15,"
      "%16, %17, %18, %19, %20, %21, %22, %23, %24, %25, %26, %27, %28, %29, %30, %31,"
      "%32, %33, %34, %35, %36, %37, %38, %39, %40, %41, %42, %43, %44, %45, %46, %47,"
      "%48, %49, %50, %51, %52, %53, %54, %55, %56, %57, %58, %59, %60, %61, %62, %63,"
      "%64, %65, %66, %67, %68, %69, %70, %71, %72, %73, %74, %75, %76, %77, %78, %79,"
      "%80, %81, %82, %83, %84, %85, %86, %87, %88, %89, %90, %91, %92, %93, %94, %95,"
      "%96, %97, %98, %99, %100, %101, %102, %103, %104, %105, %106, %107, %108, %109, %110, %111,"
      "%112, %113, %114, %115, %116, %117, %118, %119, %120, %121, %122, %123, %124, %125, %126, %127"
      "}, %128, %129, p, 1, 1, 0, %131;\n}\n"
      : "+f"(d[0]), "+f"(d[1]), "+f"(d[2]), "+f"(d[3]), "+f"(d[4]), "+f"(d[5]), "+f"(d[6]), "+f"(d[7]),
        "+f"(d[8]), "+f"(d[9]), "+f"(d[10]), "+f"(d[11]), "+f"(d[12]), "+f"(d[13]), "+f"(d[14]), "+f"(d[15]),
        "+f"(d[16]), "+f"(d[17]), "+f"(d[18]), "+f"(d[19]), "+f"(d[20]), "+f"(d[21]), "+f"(d[22]), "+f"(d[23]),
        "+f"(d[24]), "+f"(d[25]), "+f"(d[26]), "+f"(d[27]), "+f"(d[28]), "+f"(d[29]), "+f"(d[30]), "+f"(d[31]),
        "+f"(d[32]), "+f"(d[33]), "+f"(d[34]), "+f"(d[35]), "+f"(d[36]), "+f"(d[37]), "+f"(d[38]), "+f"(d[39]),
        "+f"(d[40]), "+f"(d[41]), "+f"(d[42]), "+f"(d[43]), "+f"(d[44]), "+f"(d[45]), "+f"(d[46]), "+f"(d[47]),
        "+f"(d[48]), "+f"(d[49]), "+f"(d[50]), "+f"(d[51]), "+f"(d[52]), "+f"(d[53]), "+f"(d[54]), "+f"(d[55]),
        "+f"(d[56]), "+f"(d[57]), "+f"(d[58]), "+f"(d[59]), "+f"(d[60]), "+f"(d[61]), "+f"(d[62]), "+f"(d[63]),
        "+f"(d[64]), "+f"(d[65]), "+f"(d[66]), "+f"(d[67]), "+f"(d[68]), "+f"(d[69]), "+f"(d[70]), "+f"(d[71]),
        "+f"(d[72]), "+f"(d[73]), "+f"(d[74]), "+f"(d[75]), "+f"(d[76]), "+f"(d[77]), "+f"(d[78]), "+f"(d[79]),
        "+f"(d[80]), "+f"(d[81]), "+f"(d[82]), "+f"(d[83]), "+f"(d[84]), "+f"(d[85]), "+f"(d[86]), "+f"(d[87]),
        "+f"(d[88]), "+f"(d[89]), "+f"(d[90]), "+f"(d[91]), "+f"(d[92]), "+f"(d[93]), "+f"(d[94]), "+f"(d[95]),
        "+f"(e[0]), "+f"(e[1]), "+f"(e[2]), "+f"(e[3]), "+f"(e[4]), "+f"(e[5]), "+f"(e[6]), "+f"(e[7]),
        "+f"(e[8]), "+f"(e[9]), "+f"(e[10]), "+f"(e[11]), "+f"(e[12]), "+f"(e[13]), "+f"(e[14]), "+f"(e[15]),
        "+f"(e[16]), "+f"(e[17]), "+f"(e[18]), "+f"(e[19]), "+f"(e[20]), "+f"(e[21]), "+f"(e[22]), "+f"(e[23]),
        "+f"(e[24]), "+f"(e[25]), "+f"(e[26]), "+f"(e[27]), "+f"(e[28]), "+f"(e[29]), "+f"(e[30]), "+f"(e[31])
      : "l"(descA), "l"(descB), "r"(scaleD), "n"(TB));
}
template <int TB = 1>
__device__ __forceinline__ void wgmma_ss_n192(float (&d)[96], uint64_t descA, uint64_t descB, int scaleD) {
  asm volatile("{\n.reg .pred p;\nsetp.ne.b32 p, %98, 0;\n"
      "wgmma.mma_async.sync.aligned.m64n192k16.f32.bf16.bf16 {"
      "%0, %1, %2, %3, %4, %5, %6, %7, %8, %9, %10, %11, %12, %13, %14, %15,"
      "%16, %17, %18, %19, %20, %21, %22, %23, %24, %25, %26, %27, %28, %29, %30, %31,"
      "%32, %33, %34, %35, %36, %37, %38, %39, %40, %41, %42, %43, %44, %45, %46, %47,"
      "%48, %49, %50, %51, %52, %53, %54, %55, %56, %57, %58, %59, %60, %61, %62, %63,"
      "%64, %65, %66, %67, %68, %69, %70, %71, %72, %73, %74, %75, %76, %77, %78, %79,"
      "%80, %81, %82, %83, %84, %85, %86, %87, %88, %89, %90, %91, %92, %93, %94, %95"
      "}, %96, %97, p, 1, 1, 0, %99;\n}\n"
      : "+f"(d[0]), "+f"(d[1]), "+f"(d[2]), "+f"(d[3]), "+f"(d[4]), "+f"(d[5]), "+f"(d[6]), "+f"(d[7]),
        "+f"(d[8]), "+f"(d[9]), "+f"(d[10]), "+f"(d[11]), "+f"(d[12]), "+f"(d[13]), "+f"(d[14]), "+f"(d[15]),
        "+f"(d[16]), "+f"(d[17]), "+f"(d[18]), "+f"(d[19]), "+f"(d[20]), "+f"(d[21]), "+f"(d[22]), "+f"(d[23]),
        "+f"(d[24]), "+f"(d[25]), "+f"(d[26]), "+f"(d[27]), "+f"(d[28]), "+f"(d[29]), "+f"(d[30]), "+f"(d[31]),
        "+f"(d[32]), "+f"(d[33]), "+f"(d[34]), "+f"(d[35]), "+f"(d[36]), "+f"(d[37]), "+f"(d[38]), "+f"(d[39]),
        "+f"(d[40]), "+f"(d[41]), "+f"(d[42]), "+f"(d[43]), "+f"(d[44]), "+f"(d[45]), "+f"(d[46]), "+f"(d[47]),
        "+f"(d[48]), "+f"(d[49]), "+f"(d[50]), "+f"(d[51]), "+f"(d[52]), "+f"(d[53]), "+f"(d[54]), "+f"(d[55]),
        "+f"(d[56]), "+f"(d[57]), "+f"(d[58]), "+f"(d[59]), "+f"(d[60]), "+f"(d[61]), "+f"(d[62]), "+f"(d[63]),
        "+f"(d[64]), "+f"(d[65]), "+f"(d[66]), "+f"(d[67]), "+f"(d[68]), "+f"(d[69]), "+f"(d[70]), "+f"(d[71]),
        "+f"(d[72]), "+f"(d[73]), "+f"(d[74]), "+f"(d[75]), "+f"(d[76]), "+f"(d[77]), "+f"(d[78]), "+f"(d[79]),
        "+f"(d[80]), "+f"(d[81]), "+f"(d[82]), "+f"(d[83]), "+f"(d[84]), "+f"(d[85]), "+f"(d[86]), "+f"(d[87]),
        "+f"(d[88]), "+f"(d[89]), "+f"(d[90]), "+f"(d[91]), "+f"(d[92]), "+f"(d[93]), "+f"(d[94]), "+f"(d[95])
      : "l"(descA), "l"(descB), "r"(scaleD), "n"(TB));
}
template <unsigned long long DESC, int SCALE>
__device__ __forceinline__ void wgmma_rs_n56(float (&d)[28], uint32_t a0, uint32_t a1, uint32_t a2, uint32_t a3) {
  asm volatile("{\n.reg .b64 desc;\nmov.b64 desc, %32;\n"
      "wgmma.mma_async.sync.aligned.m64n56k16.f32.bf16.bf16 {"
      "%0, %1, %2, %3, %4, %5, %6, %7, %8, %9, %10, %11, %12, %13, %14, %15,"
      "%16, %17, %18, %19, %20, %21, %22, %23, %24, %25, %26, %27"
      "}, {%28, %29, %30, %31}, desc, %33, 1, 1, 0;\n}\n"
      : "+f"(d[0]), "+f"(d[1]), "+f"(d[2]), "+f"(d[3]), "+f"(d[4]), "+f"(d[5]), "+f"(d[6]), "+f"(d[7]),
        "+f"(d[8]), "+f"(d[9]), "+f"(d[10]), "+f"(d[11]), "+f"(d[12]), "+f"(d[13]), "+f"(d[14]), "+f"(d[15]),
        "+f"(d[16]), "+f"(d[17]), "+f"(d[18]), "+f"(d[19]), "+f"(d[20]), "+f"(d[21]), "+f"(d[22]), "+f"(d[23]),
        "+f"(d[24]), "+f"(d[25]), "+f"(d[26]), "+f"(d[27])
      : "r"(a0), "r"(a1), "r"(a2), "r"(a3), "n"(DESC), "n"(SCALE));
}
template <unsigned long long DESC, int SCALE>
__device__ __forceinline__ void wgmma_rs_n32(float (&d)[28], uint32_t a0, uint32_t a1, uint32_t a2, uint32_t a3) {
  asm volatile("{\n.reg .b64 desc;\nmov.b64 desc, %20;\n"
      "wgmma.mma_async.sync.aligned.m64n32k16.f32.bf16.bf16 {"
      "%0, %1, %2, %3, %4, %5, %6, %7, %8, %9, %10, %11, %12, %13, %14, %15"
      "}, {%16, %17, %18, %19}, desc, %21, 1, 1, 0;\n}\n"
      : "+f"(d[0]), "+f"(d[1]), "+f"(d[2]), "+f"(d[3]), "+f"(d[4]), "+f"(d[5]), "+f"(d[6]), "+f"(d[7]),
        "+f"(d[8]), "+f"(d[9]), "+f"(d[10]), "+f"(d[11]), "+f"(d[12]), "+f"(d[13]), "+f"(d[14]), "+f"(d[15])
      : "r"(a0), "r"(a1), "r"(a2), "r"(a3), "n"(DESC), "n"(SCALE));
}

constexpr int NB = 4096, NF = 26, DIN = 1664;
constexpr int NGEMM = 128, NEXTRA = 4, GRID = NGEMM + NEXTRA;
constexpr int NR = 2;
constexpr int NC_WG0 = 16;
constexpr int WK = 1;
constexpr int OB = 5;
constexpr int AR = 3;
constexpr int HK = 3;
constexpr int PE0 = 14;
constexpr int WD = 2;
constexpr int GI = 3;
constexpr int PE1 = 6;
constexpr int PE2 = 12;
constexpr int PS2 = 11;
constexpr int PS = 6;
constexpr int RB = 4;
constexpr int NC_GEMM = 29, NBIG = 16 * NR, POOL = NGEMM * NC_GEMM, NC_EXTRA = (NB - POOL - NBIG) / NEXTRA;
static_assert((NR == 1 || NR == 2) && NC_WG0 == 16, "split");
constexpr int CW_MAIN = 22 * 1792, CW_LIN = 2 * 1024, CW_BYTES = CW_MAIN + CW_LIN;
constexpr int XSLOT = 4096;

constexpr int UNIT = 8192, FS = 18;
constexpr int U_W = 6, U_XB = 18, U_SP = 24;
constexpr int CW_CUT = 9;
constexpr int OFF_CW = 0, OFF_CW2 = 6 * UNIT, OFF_CWL = 9 * UNIT;
constexpr int OFF_PART = OFF_CWL + CW_LIN;
constexpr int CROW = 528;
constexpr int OFF_CIN = 2 * UNIT;
constexpr int OFF_GIDX = 26 * UNIT;
constexpr int OFF_TIDX = OFF_GIDX + 128 * NF * 4 - 8 * 64 * 4;
constexpr int OFF_CIDX = OFF_GIDX + 128 * NF * 4;
constexpr int OFF_EPI = OFF_CIDX + 30 * NF * 4;
constexpr int OFF_DNN = OFF_EPI + 128 * 16;
constexpr int OFF_BAR = OFF_DNN + 96 * 4;
constexpr int SMEM_BYTES = OFF_BAR + 66 * 8;
static_assert(CW_CUT * 1792 <= 2 * UNIT && (22 - CW_CUT) * 1792 <= 3 * UNIT && 30 * CROW <= 2 * UNIT, "smem");
constexpr uint32_t SMEM_BASE = 1024;
static_assert(SMEM_BYTES <= 232448, "smem");
static_assert(OFF_EPI % 16 == 0 && OFF_CIDX % 16 == 0 && OFF_BAR % 8 == 0, "align");
constexpr int XOFF_W3 = 0, XOFF_W2 = 35152, XOFF_W1 = 70304, XOFF_M = XOFF_W1 + 7 * 1392, XOFF_TAB = XOFF_M + 32 * 40 * 4, XOFF_S = XOFF_TAB + 3072,
              XOFF_SLOT = 10 * UNIT, XOFF_CIN0 = 2 * UNIT, XOFF_CIN1 = 18 * UNIT, XOFF_CIDX = 22 * UNIT;
static_assert(XOFF_S + 7 * 3152 <= 21 * UNIT && 46 * CROW <= 3 * UNIT, "smem");

constexpr int BAR_WIN = 7,
              BAR_FULL = 8,
              BAR_EV = 16,
              BAR_CW = 24,
              BAR_GIDX = 25, BAR_CIDX = 26,
              BAR_W0 = 27,
              BAR_DNN = 28,
              BAR_T = 29,
              BAR_GDONE = 30,
              BAR_PART = 31,
              BAR_CFULL = 32,
              BAR_POOL = BAR_CFULL + 28,
              BAR_C0 = 64;
constexpr int EV_CW = 29, EV_CIN = 30, EV_SLOT = 31, EV_END = 33;
__device__ __forceinline__ uint32_t ev_bar(uint32_t bars, int e) { return bars + 8 * (BAR_EV + (e & 7)); }
__device__ __forceinline__ uint32_t ev_par(int e) { return (e >> 3) & 1; }
__host__ __device__ constexpr int b_x(int t) { return ((0xb2c1430bu >> (4 * t)) & 15) * 2; }
__host__ __device__ constexpr int b_w(int t) { return (0x0d0a120eu >> (8 * (t & 3))) & 31; }
__host__ __device__ constexpr int b_ws(int t) { return (t & 3) == 3 ? 4 : 1; }

struct Scratch {
  uint4 cw[CW_BYTES / 16];
  float part[8 * NB];
  unsigned dflag[16 * 8];
  unsigned epoch[GRID];
  unsigned place[16 * 8];
  unsigned foldflag;
};
__device__ __align__(128) Scratch g_scratch;
struct GPtr { Scratch* s; const uint4* tab; const uint4* jobs; uint32_t zero; };

__device__ __forceinline__ void wg_fence() { asm volatile("wgmma.fence.sync.aligned;" ::: "memory"); }
__device__ __forceinline__ void wg_commit() { asm volatile("wgmma.commit_group.sync.aligned;" ::: "memory"); }
template <int N> __device__ __forceinline__ void wg_wait() { asm volatile("wgmma.wait_group.sync.aligned %0;" ::"n"(N) : "memory"); }
__device__ __forceinline__ uint64_t mkdesc(uint32_t addr, uint32_t lbo, uint32_t sbo, uint32_t swz) {
  return (uint64_t)((addr & 0x3FFFF) >> 4) | ((uint64_t)(lbo >> 4) << 16) | ((uint64_t)(sbo >> 4) << 32) | ((uint64_t)swz << 62);
}
__device__ __forceinline__ bool elect1() {
  uint32_t p; asm volatile("{\n.reg .pred p;\nelect.sync _|p, 0xffffffff;\nselp.b32 %0, 1, 0, p;\n}" : "=r"(p)); return p;
}
__device__ __forceinline__ int fresh(int v) { asm volatile("" : "+r"(v)); return v; }
__device__ __forceinline__ void sched_fence() { asm volatile("pmevent 0;" ::: "memory"); }
__device__ __forceinline__ void mbar_init(uint32_t bar, uint32_t cnt) { asm volatile("mbarrier.init.shared::cta.b64 [%0], %1;" ::"r"(bar), "r"(cnt) : "memory"); }
__device__ __forceinline__ void mbar_arrive(uint32_t bar) { asm volatile("mbarrier.arrive.shared::cta.b64 _, [%0];" ::"r"(bar) : "memory"); }
__device__ __forceinline__ void mbar_arrive_cta(uint32_t bar, uint32_t cta) {
  asm volatile("{\n.reg .b32 r;\nmapa.shared::cluster.u32 r, %0, %1;\nmbarrier.arrive.shared::cluster.b64 _, [r];\n}" ::"r"(bar), "r"(cta) : "memory");
}
__device__ __forceinline__ void mbar_expect_tx(uint32_t bar, uint32_t bytes) { asm volatile("mbarrier.arrive.expect_tx.shared::cta.b64 _, [%0], %1;" ::"r"(bar), "r"(bytes) : "memory"); }
__device__ __forceinline__ void mbar_wait(uint32_t bar, uint32_t parity) {
  asm volatile("{\n.reg .pred p;\nLAB_WAIT:\nmbarrier.try_wait.parity.shared::cta.b64 p, [%0], %1;\n@!p bra LAB_WAIT;\n}" ::"r"(bar), "r"(parity) : "memory");
}
__device__ __forceinline__ void flag_wait(const unsigned* p, unsigned target, unsigned sleep_ns) {
  asm volatile("{\n.reg .pred p;\n.reg .u32 n, v;\nmov.u32 n, 0;\nLAB_WAIT:\n"
               "ld.acquire.gpu.global.u32 v, [%0];\n"
               "sub.u32 v, v, %1;\n"
               "setp.ge.s32 p, v, 0;\n"
               "@p bra DONE;\n"
               "nanosleep.u32 %2;\n"
               "add.u32 n, n, 1;\n"
               "setp.lt.u32 p, n, 400000;\n"
               "@p bra LAB_WAIT;\n"
               "DONE:\n}" ::"l"(p), "r"(target), "r"(sleep_ns) : "memory");
}
__device__ __forceinline__ void flag_add(unsigned* p) { asm volatile("red.release.gpu.global.add.u32 [%0], 1;" ::"l"(p) : "memory"); }
__device__ __forceinline__ void tma_load(uint32_t dst, const CUtensorMap* tm, int c0, int c1, uint32_t bar) {
  asm volatile("cp.async.bulk.tensor.2d.shared::cluster.global.mbarrier::complete_tx::bytes [%0], [%1, {%3, %4}], [%2];"
               ::"r"(dst), "l"(tm), "r"(bar), "r"(c0), "r"(c1) : "memory");
}
__device__ __forceinline__ void tma_row_mc(uint32_t dst, const CUtensorMap* tm, int row, uint32_t bar) {
  asm volatile("cp.async.bulk.tensor.2d.shared::cluster.global.mbarrier::complete_tx::bytes.multicast::cluster [%0], [%1, {%3, %4}], [%2], %5;"
               ::"r"(dst), "l"(tm), "r"(bar), "r"(0), "r"(row), "h"((uint16_t)3));
}
__device__ __forceinline__ void tma_row(uint32_t dst, const CUtensorMap* tm, int row, uint32_t bar) {
  asm volatile("cp.async.bulk.tensor.2d.shared::cluster.global.mbarrier::complete_tx::bytes [%0], [%1, {%3, %4}], [%2];"
               ::"r"(dst), "l"(tm), "r"(bar), "r"(0), "r"(row));
}
__device__ __forceinline__ void bulk_load(uint32_t dst, const void* src, uint32_t bytes, uint32_t bar) {
  asm volatile("cp.async.bulk.shared::cluster.global.mbarrier::complete_tx::bytes [%0], [%1], %2, [%3];"
               ::"r"(dst), "l"(src), "r"(bytes), "r"(bar));
}
__device__ __forceinline__ void l2_prefetch(const void* src, uint32_t bytes) {
  asm volatile("cp.async.bulk.prefetch.L2.global [%0], %1;" ::"l"(src), "r"(bytes));
}
__device__ __forceinline__ void w_prefetch(const __nv_bfloat16* w1, int f, int cta, int piece) {
  l2_prefetch(w1 + (f * 64 + (cta >> 3) * 4 + (cta & 1) * 2 + (piece & 1)) * DIN + (piece < 2 ? (cta & 6) * 192 : 1536 + (cta & 4) * 16),
              piece < 2 ? 768 : 128);
}
__device__ __forceinline__ void cpasync16(uint32_t dst, const void* src) {
  asm volatile("cp.async.cg.shared.global [%0], [%1], 16;" ::"r"(dst), "l"(src) : "memory");
}
template <int ID, int N> __device__ __forceinline__ void bar_sync() { asm volatile("bar.sync %0, %1;" ::"n"(ID), "n"(N) : "memory"); }
template <int ID, int N> __device__ __forceinline__ void bar_arrive() { asm volatile("bar.arrive %0, %1;" ::"n"(ID), "n"(N) : "memory"); }
__device__ __forceinline__ void ldsm4t(uint32_t& a, uint32_t& b, uint32_t& c, uint32_t& d, uint32_t addr) {
  asm volatile("ldmatrix.sync.aligned.m8n8.x4.trans.shared.b16 {%0,%1,%2,%3}, [%4];" : "=r"(a), "=r"(b), "=r"(c), "=r"(d) : "r"(addr) : "memory");
}
__device__ __forceinline__ void ldsm2t(uint32_t& a, uint32_t& b, uint32_t addr) {
  asm volatile("ldmatrix.sync.aligned.m8n8.x2.trans.shared.b16 {%0,%1}, [%2];" : "=r"(a), "=r"(b) : "r"(addr) : "memory");
}
__device__ __forceinline__ int lds32(uint32_t addr) { int v; asm volatile("ld.shared.b32 %0, [%1];" : "=r"(v) : "r"(addr)); return v; }
__device__ __forceinline__ int2 lds64(uint32_t addr) { int2 v; asm volatile("ld.shared.v2.b32 {%0,%1}, [%2];" : "=r"(v.x), "=r"(v.y) : "r"(addr)); return v; }
__device__ __forceinline__ int4 lds128(uint32_t addr) {
  int4 v; asm volatile("ld.shared.v4.b32 {%0,%1,%2,%3}, [%4];" : "=r"(v.x), "=r"(v.y), "=r"(v.z), "=r"(v.w) : "r"(addr)); return v;
}
__device__ __forceinline__ float4 lds128f(uint32_t addr) {
  float4 v; asm volatile("ld.shared.v4.f32 {%0,%1,%2,%3}, [%4];" : "=f"(v.x), "=f"(v.y), "=f"(v.z), "=f"(v.w) : "r"(addr) : "memory"); return v;
}
__device__ __forceinline__ void sts32f(uint32_t addr, float v) { asm volatile("st.shared.f32 [%0], %1;" ::"r"(addr), "f"(v) : "memory"); }
__device__ __forceinline__ float bf_lo(uint32_t v) { return __uint_as_float(v << 16); }
__device__ __forceinline__ float bf_hi(uint32_t v) { return __uint_as_float(v & 0xffff0000u); }
__device__ __forceinline__ float bf2f(__nv_bfloat16 v) { return __bfloat162float(v); }

__device__ __forceinline__ uint32_t mul2(uint32_t a, uint32_t b) {
  uint32_t r; asm volatile("mul.rn.bf16x2 %0, %1, %2;" : "=r"(r) : "r"(a), "r"(b)); return r;
}
__device__ __forceinline__ uint32_t mul2lo(uint32_t a, uint32_t b) {
  uint32_t r;
  asm volatile("{\n.reg .b16 l, h;\n.reg .b32 t;\nmov.b32 {l, h}, %2;\nmov.b32 t, {l, l};\nmul.rn.bf16x2 %0, %1, t;\n}" : "=r"(r) : "r"(a), "r"(b));
  return r;
}
__device__ __forceinline__ uint32_t mul2hi(uint32_t a, uint32_t b) {
  uint32_t r;
  asm volatile("{\n.reg .b16 l, h;\n.reg .b32 t;\nmov.b32 {l, h}, %2;\nmov.b32 t, {h, h};\nmul.rn.bf16x2 %0, %1, t;\n}" : "=r"(r) : "r"(a), "r"(b));
  return r;
}

__host__ __device__ constexpr int xfield(int r, int e, int c) {
  return r == 9 ? 24 + e : 8 * (r / 3) + 2 * (((r % 3) + c) & 3) + (((r % 3) == 2 && c >= 2) ? 1 - e : e);
}
__host__ __device__ constexpr int blk_a(int b) { return b < 12 ? 3 * (b / 8) + ((b & 3) == 3) : (b < 15 ? 3 * (b - 12) : 3 * (b - 15)); }
__host__ __device__ constexpr int blk_b(int b) { return b < 12 ? 3 * (b < 4 ? 1 : 2) + ((b & 3) == 3 ? 0 : (b & 3)) : (b < 15 ? 3 * (b - 12) + 1 : 9); }
__host__ __device__ constexpr int slot_pq(int u, int e, int c) {
  return u < 36 ? (xfield(blk_a(u >> 1), e, c) | (xfield(blk_b(u >> 1), u & 1, c) << 8))
       : u < 39 ? (xfield(3 * (u - 36), e, c) | (xfield(3 * (u - 36), 0, c) << 8))
       : u < 42 ? (xfield(3 * (u - 39), e, c) | (xfield(3 * (u - 39) + 2, e, c) << 8))
       : u == 42 ? (xfield(3 * e, 1, c) * 257)
       : u == 43 ? (e == 0 ? (xfield(6, 1, c) * 257)
                           : (c == 0 ? 24 * 257 : c == 1 ? 25 * 257 : c == 2 ? (24 | 25 << 8) : 26 * 257))
       : u < 47 ? (xfield(3 * (u - 44), e, c) | (26 << 8))
       : (c == 0 ? ((24 + e) | 26 << 8) : c == 3 ? ((26 + e) | (27 - e) << 8) : 27 * 257);
}
struct SlotTab { uint32_t v[2 * 48 * 8]; };
constexpr SlotTab make_slot_tab() {
  SlotTab t{};
  for (int u = 0; u < 48; u++)
    for (int k = 0; k < 8; k++) {
      const int pq = slot_pq(u, k & 1, k >> 1), p = pq & 255, q = pq >> 8;
      t.v[u * 8 + k] = (uint32_t)((p * 28 + q) * 4) | ((uint32_t)(((p != q && q < 26) ? q * 28 + p : 27 * 28 + 27) * 4) << 16);
      t.v[384 + u * 8 + k] = (uint32_t)(q < 26 ? (p * 26 + q) * 2 : 1360) | ((uint32_t)((p != q && q < 26) ? (q * 26 + p) * 2 : 1360) << 16);
    }
  return t;
}
__device__ __align__(16) const SlotTab g_slot_tab = make_slot_tab();

struct CinCtx {
  uint32_t tab0, tab1, full, fmask, it, lim, co, sb;
  uint32_t cin, o03, o14, o25, o9, o78, selA, selB;
  bool ones, lead;
};
constexpr unsigned long long CW_DESC = (unsigned long long)((SMEM_BASE + OFF_CW) >> 4) | (8ull << 16) | (16ull << 32);
constexpr int OFF_INIT = U_SP * UNIT;
constexpr unsigned long long INIT_DESC = (unsigned long long)((SMEM_BASE + OFF_INIT) >> 4) | (9ull << 32);
constexpr unsigned long long ONES_DESC = (SMEM_BASE + OFF_INIT + 4608) >> 4;
constexpr unsigned long long CWL_DESC = CW_DESC + (OFF_CWL - OFF_CW) / 16;

template <int U>
__device__ __forceinline__ uint32_t zreg(uint32_t (&x)[11][2], int h, const CinCtx& c) {
  if constexpr (U < 36) {
    if constexpr (U & 1) return mul2hi(x[blk_a(U >> 1)][h], x[blk_b(U >> 1)][h]);
    else return mul2lo(x[blk_a(U >> 1)][h], x[blk_b(U >> 1)][h]);
  } else if constexpr (U < 39) {
    return mul2lo(x[3 * (U - 36)][h], x[3 * (U - 36)][h]);
  } else if constexpr (U < 42) {
    return mul2(x[3 * (U - 39)][h], x[3 * (U - 39) + 2][h]);
  } else if constexpr (U == 42) {
    const uint32_t p = __byte_perm(x[0][h], x[3][h], 0x7632);
    return mul2(p, p);
  } else {
    x[10][h] = c.ones ? 0x3f803f80u : x[9][h];
    return mul2(__byte_perm(x[6][h], x[10][h], c.selA), __byte_perm(x[6][h], x[10][h], c.selB));
  }
}

__host__ __device__ constexpr int kord(int s) { return s == 0 ? 21 : s < 4 ? 14 + s : s < 19 ? s - 4 : s - 1; }
template <int S0, int NS>
struct ZGroup {
  uint32_t z[NS][4];
  template <int I = 0>
  __device__ __forceinline__ void fill(uint32_t (&x)[11][2], const CinCtx& c) {
    if constexpr (I < NS) {
      z[I][0] = zreg<2 * kord(S0 + I)>(x, 0, c);
      z[I][1] = zreg<2 * kord(S0 + I)>(x, 1, c);
      z[I][2] = zreg<2 * kord(S0 + I) + 1>(x, 0, c);
      z[I][3] = zreg<2 * kord(S0 + I) + 1>(x, 1, c);
      fill<I + 1>(x, c);
    }
  }
  template <int I = 0>
  __device__ __forceinline__ void mma(float (&acc)[28]) {
    if constexpr (I < NS) {
      constexpr int S = kord(S0 + I);
      wgmma_rs_n56<CW_DESC + (S < CW_CUT ? S * 1792 : OFF_CW2 - OFF_CW + (S - CW_CUT) * 1792) / 16, (S0 + I) != 0>(acc, z[I][0], z[I][1], z[I][2], z[I][3]);
      mma<I + 1>(acc);
    }
  }
};

__device__ __forceinline__ void cin_finish(const CinCtx& c, float (&acc)[28], uint32_t out) {
#pragma unroll
  for (int i = 0; i < 28; i++) asm volatile("" : "+f"(acc[i]));
  float s0 = acc[12] * acc[13], s1 = acc[14] * acc[15];
#pragma unroll
  for (int i = 0; i < 12; i += 2) {
    s0 = fmaf(acc[i], acc[16 + i], s0);
    s1 = fmaf(acc[i + 1], acc[17 + i], s1);
  }
  sts32f(out, s0 + s1);
}

__device__ __forceinline__ void cin_ldsm(const CinCtx& c, uint32_t so, uint32_t (&x)[11][2], int i) {
  if (i == 0) ldsm4t(x[0][0], x[0][1], x[3][0], x[3][1], so + c.o03);
  if (i == 1) ldsm2t(x[6][0], x[6][1], so + c.o03 + 2048);
  if (i == 1) ldsm2t(x[9][0], x[9][1], so + c.o9 + 3072);
  if (i == 2) ldsm4t(x[1][0], x[1][1], x[4][0], x[4][1], so + c.o14);
  if (i == 3) ldsm4t(x[2][0], x[2][1], x[5][0], x[5][1], so + c.o25);
  if (i == 4) ldsm4t(x[7][0], x[7][1], x[8][0], x[8][1], so + c.o78 + 2048);
}
__device__ __forceinline__ bool cin_late(const CinCtx& c, int k) {
  uint32_t ok = 1;
  asm volatile("{\n.reg .pred p;\nmbarrier.test_wait.parity.shared::cta.b64 p, [%1], %2;\nselp.b32 %0, 1, 0, p;\n}"
               : "=r"(ok) : "r"(c.full + (c.it & c.fmask) + 8 * k), "r"((((c.it & ~c.fmask) << 25) ^ (c.lim - 9 - 8 * k - c.it)) >> 31) : "memory");
  return !ok;
}
__device__ __forceinline__ void cin_load(const CinCtx& c, int k, bool late, uint32_t (&x)[11][2]) {
  const uint32_t fb = c.full + (c.it & c.fmask) + 8 * k;
  if (__builtin_expect(late, 0)) mbar_wait(fb, ((c.it & ~c.fmask) >> 6) & 1);
#pragma unroll
  for (int i = 0; i < 5; i++) cin_ldsm(c, c.sb + (c.tab0 & 31) * UNIT + k * XSLOT, x, i);
  if (c.lead) mbar_arrive(fb + 64);
}
__device__ __forceinline__ void cin_advance(CinCtx& c) {
  const uint32_t t = __funnelshift_r(c.tab0, c.tab1, 8);
  c.tab1 = __funnelshift_r(c.tab1, c.tab0, 8);
  c.tab0 = t;
  c.it += 16;
  c.co += 2 * CROW;
}
constexpr int CG_SIZE = 2;
constexpr int CG_WAIT = 4;
constexpr int CG_HEAD = 4;
constexpr int CG_LOAD = 4;
constexpr int CG_N = (22 + CG_SIZE - 1) / CG_SIZE;
constexpr int CG_ASK = 4;
constexpr int CG_HW = 3;
template <int G, int GEND>
__device__ __forceinline__ void cin_groups(const CinCtx& c, uint32_t (&x)[11][2], float (&acc)[28],
                                           int q, bool& late, uint32_t (&xn)[11][2]) {
  if constexpr (G < GEND) {
    constexpr int S0 = G * CG_SIZE, NS = (S0 + CG_SIZE <= 22) ? CG_SIZE : 22 - S0;
    if constexpr (G == CG_ASK) late = cin_late(c, q);
    ZGroup<S0, NS> g; g.fill(x, c);
    wg_fence();
    g.mma(acc);
    wg_commit();
    if constexpr (G == CG_N - 1) {
      wg_fence();
      wgmma_rs_n32<CWL_DESC, 1>(acc, x[0][0], x[0][1], x[3][0], x[3][1]);
      wgmma_rs_n32<CWL_DESC + 1024 / 16, 1>(acc, x[6][0], x[6][1], x[10][0], x[10][1]);
      wg_commit();
    }
    if constexpr (G == CG_LOAD) cin_load(c, q, late, xn);
    if constexpr (G != CG_HEAD - 1) {
      if constexpr (G == CG_N - 1 || G < CG_HW) wg_wait<CG_WAIT + 1>(); else wg_wait<CG_WAIT>();
    }
    cin_groups<G + 1, GEND>(c, x, acc, q, late, xn);
  }
}
__device__ __forceinline__ void cin_head(const CinCtx& c, uint32_t (&x)[11][2], float (&acc)[28], int q, bool& late) {
  cin_groups<0, CG_HEAD>(c, x, acc, q, late, x);
}
__device__ __forceinline__ void cin_tail(const CinCtx& c, uint32_t (&x)[11][2], float (&acc)[28],
                                         int q, bool& late, uint32_t (&xn)[11][2]) {
  cin_groups<CG_HEAD, CG_N>(c, x, acc, q, late, xn);
}

__device__ __forceinline__ void cin_setup(CinCtx& c, uint32_t sb, int wg, int tid, bool gemm, int nj) {
  c.tab0 = !gemm ? 0x0d0c0b0a + wg * 0x04040404 : wg ? 0x0d0c0b0a : 0x100f0e1a;
  c.tab1 = !gemm ? c.tab0 : wg ? 0x17171615 : 0x14131211;
  c.full = sb + OFF_BAR + 8 * (BAR_CFULL + wg * 16);
  c.fmask = gemm ? 0x70 : 0x30;
  c.it = 0; c.lim = 8 * nj; c.sb = sb;
  c.lead = (tid & 31) == 0 && !gemm;
  const uint32_t f0 = tid & 7, ch = (tid & 0x60) | ((tid & 8) << 1), chm = ch | ((tid & 16) << 6);
  c.o03 = (f0 * 144) ^ chm;
  c.o14 = (((f0 + 2) & 7) * 144) ^ chm;
  c.o25 = c.o03 ^ (tid & 4 ? 5 * 144 : 4 * 144);
  c.o9 = ((tid & 1) * 144) ^ ch;
  c.o78 = tid & 16 ? c.o25 - 1024 : c.o14;
  const int q = tid & 3;
  c.selA = q == 1 ? 0x7632 : 0x5432;
  c.selB = q == 0 ? 0x5432 : 0x7632;
  c.ones = q == 3;
}
template <typename F0, typename F, typename F2>
__device__ __forceinline__ void cin_run(CinCtx& c, F0 first_load, F after_start, F2 before_end) {
  float accA[28], accB[28];
  uint32_t xA[11][2], xB[11][2];
  first_load(xA);
  bool late;
  cin_head(c, xA, accA, 0, late);
  after_start();
#pragma unroll 1
  for (;;) {
    const uint32_t out = c.cin + c.co;
    cin_tail(c, xA, accA, 0, late, xB);
    if (c.it + 8 >= c.lim) { before_end(false); wg_wait<0>(); cin_finish(c, accA, out); break; }
    cin_head(c, xB, accB, 1, late);
    wg_wait<CG_HEAD>();
    cin_finish(c, accA, out);
    cin_tail(c, xB, accB, 1, late, xA);
    cin_advance(c);
    if (c.it >= c.lim) { before_end(true); wg_wait<0>(); cin_finish(c, accB, out + CROW); break; }
    cin_head(c, xA, accA, 0, late);
    wg_wait<CG_HEAD>();
    cin_finish(c, accB, out + CROW);
  }
}

constexpr float ALPHA = 0.3292034911525734f, KAPPA = 2.423681954311584f;

constexpr int GD = 1;
constexpr int GK = 0;
constexpr int TK = 2;
constexpr int GL = 2;
template <int NG>
struct Gelu {
  float4 q[NG / 2];
  float u[4 * NG];
  float ab;
  uint32_t ep;
  static constexpr int END = NG + GD + 4;
  __device__ __forceinline__ void start(uint32_t a, uint32_t sb) {
    ep = a;
    ab = __int_as_float(lds32(sb + OFF_EPI + 1024));
  }
  __device__ __forceinline__ void take(const Gelu& o) {
#pragma unroll
    for (int m = TK; m < NG / 2; m++)
      asm volatile("mov.b32 %0, %4;\nmov.b32 %1, %5;\nmov.b32 %2, %6;\nmov.b32 %3, %7;"
                   : "=f"(q[m].x), "=f"(q[m].y), "=f"(q[m].z), "=f"(q[m].w) : "f"(o.q[m].x), "f"(o.q[m].y), "f"(o.q[m].z), "f"(o.q[m].w));
    ab = o.ab;
  }
  struct Nop { __device__ __forceinline__ void operator()(int) const {} };
  template <int I0, int I1, bool LOAD = true, typename F = Nop>
  __device__ __forceinline__ void part(float (&d)[4 * NG], float& r0, float& r1, F hook = F()) {
#pragma unroll
    for (int i = I0; i < I1; i++) {
      sched_fence();
      hook(i - I0);
#pragma unroll
      for (int m = 0; m < NG / 2; m++)
        if ((LOAD || m < TK) && i == 2 * m + GD + 4 - (m < 2 ? 2 : GL)) q[m] = lds128f(ep + m * 64);
#pragma unroll
      for (int e = 0; e < 4; e++) {
        const int k0 = 4 * i + e, k1 = k0 - 4, k2 = k0 - 8, k3 = k0 - 12, k4 = k3 - 4 * GD, k5 = k4 - 4;
        if (k3 >= 0 && k3 < 4 * NG) asm volatile("tanh.approx.f32 %0, %0;" : "+f"(u[k3]));
        if (k5 >= 0) {
          const float4 v = q[k5 >> 3];
          float& r = e & 2 ? r1 : r0;
          asm volatile("fma.rn.f32 %0, %1, %2, %0;" : "+f"(r) : "f"(d[k5]), "f"(k5 & 4 ? (e & 1 ? v.w : v.z) : (e & 1 ? v.y : v.x)));
        }
        if (k4 >= 0 && k4 < 4 * NG) asm volatile("fma.rn.f32 %0, %0, %1, %0;" : "+f"(d[k4]) : "f"(u[k4]));
        if (k2 >= 0 && k2 < 4 * NG) asm volatile("mul.rn.f32 %0, %0, %1;" : "+f"(u[k2]) : "f"(d[k2]));
        if (k1 >= 0 && k1 < 4 * NG) asm volatile("fma.rn.f32 %0, %1, %1, %2;" : "=f"(u[k1]) : "f"(d[k1]), "f"(KAPPA));
        if (k0 < 4 * NG) asm volatile("fma.rn.f32 %0, %0, %1, %2;" : "+f"(d[k0]) : "f"(ALPHA), "f"(ab));
      }
    }
    sched_fence();
  }
};
__device__ __forceinline__ void pin(float a, float b, uint32_t addr, uint32_t zero) {
  asm volatile("{\n.reg .pred p;\nsetp.ne.u32 p, %3, 0;\n@p st.shared.v2.f32 [%0], {%1, %2};\n}" ::"r"(addr), "f"(a), "f"(b), "r"(zero) : "memory");
}
__device__ __forceinline__ void hand_on(float (&d)[96], const float (&s)[96]) {
#pragma unroll
  for (int i = 0; i < 96; i++) asm volatile("mov.b32 %0, %1;" : "=f"(d[i]) : "f"(s[i]));
}
__device__ __forceinline__ uint64_t desc_x(int u) { return mkdesc(SMEM_BASE, 16, 1024, 1) + u * (UNIT / 16); }
__device__ __forceinline__ uint64_t desc_w(int u, int stride = 1) { return mkdesc(SMEM_BASE, stride * UNIT, 1024, 1) + u * (UNIT / 16); }
__device__ __forceinline__ void tile_step(float (&d)[96], uint64_t dA, uint64_t dB) {
  wg_fence();
#pragma unroll
  for (int k = 0; k < 4; k++) wgmma_ss_n192(d, dA + 2 * k, dB + 128 * k, 1);
  wg_commit();
}
template <int K0 = 0, int K1 = 4>
__device__ __forceinline__ void wide_step(float (&d)[96], float (&e)[32], uint64_t dA, uint64_t dB) {
  wg_fence();
#pragma unroll
  for (int k = K0; k < K1; k++) wgmma_ss_n256(d, e, dA + 2 * k, dB + 128 * k, 1);
  wg_commit();
}
constexpr int slot_of(int wg, int j) {
  return wg ? (j == 0 ? 24 * UNIT : j <= 8 ? 10 * UNIT + (j - 1) * XSLOT : 21 * UNIT + (j - 9) * XSLOT)
            : (j == 0 ? OFF_GIDX + 2 * XSLOT : (j < 3 ? OFF_GIDX + 2 * XSLOT : 14 * UNIT) + (j - 3) * XSLOT);
}
constexpr int NLW = 3;
constexpr int NE = 10;
constexpr int LB = 1;
struct alignas(8) Job { uint32_t wait, par, slot, full, idx, next; };
constexpr int OFF_WIN = OFF_EPI + 1028, OFF_JOB = OFF_EPI + 1040, OFF_PIDX = OFF_JOB + 32 * sizeof(Job), XOFF_JOB = 24 * UNIT, XOFF_DNN = 25 * UNIT;
static_assert(OFF_PIDX + 2 * NF * 4 <= OFF_DNN, "smem");
struct JobTab { Job v[2][32 + NC_EXTRA]; };
constexpr Job make_job(int rank, int wait, int par, int slot, int full, int idx, int next) {
  const uint32_t sb = SMEM_BASE + (rank << 24);
  return Job{sb + OFF_BAR + 8 * wait, uint32_t(par), sb + slot, sb + OFF_BAR + 8 * full, sb + idx, next ? sb + next : 0};
}
constexpr JobTab make_jobs() {
  JobTab t{};
  int m = 0;
  for (int n = 0; n < 36; n++) {
    const int wg = n < 7 ? n == 4 : n & 1, j = n < 4 ? n : n < 7 ? n - 1 - 3 * wg : wg ? n / 2 - 2 : n / 2 + 2, s = wg * NC_WG0 + j;
    if (s >= NC_GEMM + NR || j >= NC_WG0) continue;
    const int e = n < 7 ? EV_SLOT : EV_END;
    for (int odd = 0; odd < 2; odd++)
      t.v[odd][m] = make_job(odd, n < 3 ? BAR_GDONE : n < NE ? BAR_EV + (e & 7) : BAR_PART, n < 3 ? 0 : (e >> 3) & 1, s > NC_GEMM ? 25 * UNIT : slot_of(wg, j),
                                   s >= NC_GEMM ? BAR_POOL : j ? BAR_CFULL + wg * 16 + j - 1 : BAR_C0 + wg,
                                   s >= NC_GEMM ? OFF_PIDX + (s - NC_GEMM + (NR == 1 && odd)) * NF * 4 : OFF_CIDX + (s + odd) * NF * 4,
                             m + NLW < NC_GEMM + NR ? OFF_JOB + (m + NLW) * sizeof(Job) : 0);
    m++;
  }
  for (int n = 0; n < NC_EXTRA; n++) {
    const int wg = n & 1, j = n >> 1, bi = (j - 1) & 7;
    for (int odd = 0; odd < 2; odd++)
      t.v[odd][32 + n] = make_job(odd, j == 0 ? BAR_GDONE : j <= 8 ? BAR_EV + (EV_END & 7) : BAR_CFULL + wg * 16 + 8 + bi, j <= 8 ? 0 : (((j - 1) >> 3) & 1) ^ 1,
                           j ? XOFF_SLOT + (wg * 8 + bi) * XSLOT : OFF_GIDX + wg * XSLOT, j ? BAR_CFULL + wg * 16 + bi : BAR_C0 + wg,
                           XOFF_CIDX + (wg * NC_EXTRA / 2 + j) * NF * 4, n + 4 < NC_EXTRA ? XOFF_JOB + (n + 4) * sizeof(Job) : 0);
  }
  return t;
}
__device__ __align__(16) const JobTab g_jobs = make_jobs();
static_assert(((EV_END >> 3) & 1) == 0, "parity");

__device__ __forceinline__ int cin_start(int c) { return c < NGEMM ? c * NC_GEMM : NB - (GRID - c) * NC_EXTRA; }
__device__ __forceinline__ int group_of(int c) { return (c < 8 ? 4 + (c >> 1) : c < 72 ? (c - 8) >> 4 : (c - 16) / 14) * 2 + (c & 1); }

__device__ __forceinline__ int fold_i0(int e) { return e < 2 ? 7 * e : 2 + 6 * e; }
__device__ __forceinline__ uint32_t ldg16(const void* p) { uint16_t v; asm volatile("ld.global.nc.u16 %0, [%1];" : "=h"(v) : "l"(p)); return v; }
__device__ __forceinline__ uint32_t ldg32(const void* p) { uint32_t v; asm volatile("ld.global.nc.u32 %0, [%1];" : "=r"(v) : "l"(p)); return v; }
__device__ __forceinline__ uint4 ldg128(const void* p) {
  uint4 v; asm volatile("ld.global.nc.v4.u32 {%0,%1,%2,%3}, [%4];" : "=r"(v.x), "=r"(v.y), "=r"(v.z), "=r"(v.w) : "l"(p)); return v;
}
__device__ __forceinline__ void sts64f(uint32_t addr, float a, float b) { asm volatile("st.shared.v2.f32 [%0], {%1, %2};" ::"r"(addr), "f"(a), "f"(b) : "memory"); }
__device__ __forceinline__ float to_tf32(float v) { uint32_t r; asm("cvt.rna.tf32.f32 %0, %1;" : "=r"(r) : "f"(v)); return __uint_as_float(r); }
__device__ __forceinline__ float lds_bf(uint32_t addr) { uint16_t v; asm volatile("ld.shared.u16 %0, [%1];" : "=h"(v) : "r"(addr)); return __uint_as_float((uint32_t)v << 16); }
template <bool RAW>
__device__ __forceinline__ uint4 fold_chunk(uint32_t base, uint32_t tab) {
  const int4 t0 = lds128(tab), t1 = lds128(tab + 16);
  const uint32_t t[8] = {uint32_t(t0.x), uint32_t(t0.y), uint32_t(t0.z), uint32_t(t0.w), uint32_t(t1.x), uint32_t(t1.y), uint32_t(t1.z), uint32_t(t1.w)};
  float w[16];
#pragma unroll
  for (int k = 0; k < 16; k++) {
    const uint32_t a = base + (k & 1 ? t[k >> 1] >> 16 : t[k >> 1] & 0xffff);
    w[k] = RAW ? lds_bf(a) : __int_as_float(lds32(a));
  }
  uint32_t v[4];
#pragma unroll
  for (int c = 0; c < 4; c++) {
    __nv_bfloat162 pk = __floats2bfloat162_rn(w[4 * c] + w[4 * c + 1], w[4 * c + 2] + w[4 * c + 3]);
    v[c] = *reinterpret_cast<uint32_t*>(&pk);
  }
  return make_uint4(v[0], v[1], v[2], v[3]);
}
__device__ __forceinline__ int cw_chunk(int u, int n) {
  return ((u < 44 ? (u >> 1) * 1792 : CW_MAIN + ((u - 44) >> 1) * 1024) + (n >> 3) * 256 + (u & 1) * 128 + (n & 7) * 16) >> 4;
}
__device__ __forceinline__ float log2_sigma(uint32_t v, int n) {
  return __reduce_add_sync(0xffffffffu, (v & 0x7fff) + ((v >> 16) & 0x7fff)) * (1.f / (128 * n)) - 126.02f;
}
__device__ __forceinline__ uint32_t acc_offset(float lg, float cap) { return __float2int_rd(fminf(fmaxf(lg + 131.5f, 0.f), cap + 127.f)) << 7 | 0x2b; }
template <typename F>
__device__ __forceinline__ void fold_weights(F keep, int warp, uint32_t sb, int e, const __nv_bfloat16* __restrict__ wco,
                                             const __nv_bfloat16* __restrict__ ws, const __nv_bfloat16* __restrict__ table, const GPtr gp) {
  const int tid = threadIdx.x, lane = tid & 31;
  const uint32_t bars = sb + OFF_BAR;
  const uint32_t wc16 = ldg16(wco + (lane < NF ? 52 + lane : 0));
  sched_fence();
  const int i0 = fold_i0(e), ni = fold_i0(e + 1) - i0, i = i0 + warp;
  const bool own = warp < ni;
  const uint32_t wb16 = ldg16(wco + (lane < NF ? 26 + lane : 0)), wa16 = ldg16(wco + (lane < NF ? lane : 0));
  const uint32_t sx = ldg32(table + lane * 8), s2 = ldg32(ws + 17576 + lane * 8), s3 = ldg32(ws + 2 * 17576 + lane * 8);
  asm volatile("barrier.cluster.arrive.relaxed.aligned;" ::: "memory");
  bar_sync<7, 288>();
  keep();
  const int ii = lane & 7, ic = i0 + ii;
  auto a_round = [&](int k) {
    const uint4 v = fold_chunk<true>(sb + XOFF_W1 + (ii < ni ? ii * 1392 + (ic & 1) * 8 : 0), sb + XOFF_TAB + 1536 + k * 128 + (lane >> 3) * 32);
    if (ii < ni && (k < 11 || ic >= 24)) gp.s->cw[cw_chunk(lane >> 3, ic < 24 ? 32 + ic : 2 * ic - 23) + k * 224 - (k == 11 ? (lane >> 4) * 48 : 0)] = v;
  };
  if (warp >= 6) {
    if (tid < 192 + 7) asm volatile("st.shared.v4.b32 [%0], {%1, %1, %1, %1};" ::"r"(sb + XOFF_W1 + (tid - 192) * 1392 + 1360), "r"(0) : "memory");
    sts64f(sb + XOFF_M + 26 * 160 + (tid - 192) * 8, 0.f, 0.f);
    if (tid < 256 - 8) sts64f(sb + XOFF_M + 26 * 160 + (tid - 128) * 8, 0.f, 0.f);
    if (tid < 192 + 48) gp.s->cw[cw_chunk(tid - 192, 28 + e)] = make_uint4(0, 0, 0, 0);
    if (tid < 192 + NF) {
      sts64f(sb + XOFF_M + lane * 160 + 104, bf_lo(wb16), 0.f);
      sts64f(sb + XOFF_M + lane * 160 + 112, 0.f, 0.f);
      sts64f(sb + XOFF_M + lane * 160 + 120, 0.f, 0.f);
    }
    if (warp == 7) {
      const float lx = log2_sigma(sx, 64) + 4.7f, l1 = log2_sigma(lane < NF ? wa16 : 0, NF), l2 = log2_sigma(lane < NF ? wb16 : 0, NF);
      const float l3 = log2_sigma(lane < NF ? wc16 : 0, NF) + log2_sigma(s3, 64) + lx;
      const float ct = bf_lo(acc_offset(fmaxf(l1, fmaxf(l2, l3) + log2_sigma(s2, 64) + lx), 100.f));
      const float w1i = __shfl_sync(0xffffffffu, bf_lo(wa16), ic);
      if (lane < 16 && ii < ni) sts64f(sb + XOFF_S + ii * 3152 + (26 + (lane >> 3)) * 112 + 104, lane < 8 ? ct : w1i, lane < 8 ? -ct : 0.f);
    }
    bar_sync<5, 64>();
    mbar_wait(bars + 8 * BAR_W0, 0);
    if (warp == 7) bar_arrive<4, 256>();
#pragma unroll 1
    for (int k = warp == 6 ? 0 : AR; k < (warp == 6 ? AR : 12); k++) a_round(k);
  } else {
    const uint32_t a = sb + XOFF_W3 + (tid < 169 ? tid : 0) * 8;
    const int o = tid * 2, o2 = o + 1;
    const uint32_t mo = sb + XOFF_M + (o / 13) * 160 + (o % 13) * 8, mo2 = sb + XOFF_M + (o2 / 13) * 160 + (o2 % 13) * 8;
    mbar_wait(bars + 8 * BAR_GIDX, 0);
    float m0 = 0.f, m1 = 0.f, m2 = 0.f, m3 = 0.f;
#pragma unroll 1
    for (int g0 = 0; g0 < NF; g0 += 13) {
      int2 v[13];
      float w[13];
#pragma unroll
      for (int g = 0; g < 13; g++) { v[g] = lds64(a + (g0 + g) * 1352); w[g] = __shfl_sync(0xffffffffu, bf_lo(wc16), g0 + g); }
#pragma unroll
      for (int g = 0; g < 13; g++) {
        m0 = fmaf(w[g], bf_lo(v[g].x), m0); m1 = fmaf(w[g], bf_hi(v[g].x), m1);
        m2 = fmaf(w[g], bf_lo(v[g].y), m2); m3 = fmaf(w[g], bf_hi(v[g].y), m3);
      }
    }
    if (tid < 169) {
      sts64f(mo, to_tf32(m0), to_tf32(m1));
      sts64f(mo2, to_tf32(m2), to_tf32(m3));
    }
  }
  if (warp < 7) {
  const uint32_t sT = sb + XOFF_S + (own ? warp : 0) * 3152;
  const int g = lane >> 2, c = lane & 3;
  uint32_t af[2][8];
  mbar_wait(bars + 8 * BAR_FULL, 0);
#pragma unroll
  for (int k = 0; k < 8; k++) {
    const int h = 4 * k + c;
    const uint32_t a = sb + XOFF_W2 + ((h < NF ? h : 0) * 676 + (own ? i : 0) * 26 + 2 * g) * 2;
    af[0][k] = lds32(a);
    af[1][k] = lds32(a + (g < 5 ? 32 : 0));
  }
  bar_sync<4, 256>();
  if (own) {
    float d[4][2][4] = {};
#pragma unroll
    for (int ks = 0; ks < 4; ks++) {
#pragma unroll
      for (int n = 0; n < 4; n++) {
        const uint32_t b0 = lds32(sb + XOFF_M + (8 * ks + c) * 160 + (8 * n + g) * 4);
        const uint32_t b1 = lds32(sb + XOFF_M + (8 * ks + c + 4) * 160 + (8 * n + g) * 4);
#pragma unroll
        for (int m = 0; m < 2; m++)
          asm("mma.sync.aligned.m16n8k8.row.col.f32.tf32.tf32.f32 {%0,%1,%2,%3}, {%4,%5,%6,%7}, {%8,%9}, {%0,%1,%2,%3};"
              : "+f"(d[n][m][0]), "+f"(d[n][m][1]), "+f"(d[n][m][2]), "+f"(d[n][m][3])
              : "r"(af[m][2 * ks] << 16), "r"(af[m][2 * ks] & 0xffff0000u), "r"(af[m][2 * ks + 1] << 16),
                "r"(af[m][2 * ks + 1] & 0xffff0000u), "r"(b0), "r"(b1));
      }
    }
#pragma unroll
    for (int n = 0; n < 4; n++) {
      if (n < 3 || c < 2) {
        const uint32_t a = sT + 2 * g * 112 + (8 * n + 2 * c) * 4;
        sts64f(a, d[n][0][0], d[n][0][1]);
        sts64f(a + 112, d[n][0][2], d[n][0][3]);
        if (g < 5) {
          sts64f(a + 16 * 112, d[n][1][0], d[n][1][1]);
          sts64f(a + 17 * 112, d[n][1][2], d[n][1][3]);
        }
      }
    }
  }
  bar_sync<5, 224>();
#pragma unroll 1
  for (int k = warp; k < 12; k += 7) {
    const uint4 v = fold_chunk<false>(sb + XOFF_S + (ii < ni ? ii : 0) * 3152, sb + XOFF_TAB + k * 128 + (lane >> 3) * 32);
    if (ii < ni) gp.s->cw[cw_chunk(lane >> 3, ic < 24 ? ic : 2 * ic - 24) + k * 224 - (k == 11 ? (lane >> 4) * 48 : 0)] = v;
  }
  }
  __syncwarp();
  if (lane == 0) flag_add(&gp.s->foldflag);
  asm volatile("barrier.cluster.wait.acquire.aligned;" ::: "memory");
  bar_sync<4, 256>();
  mbar_wait(bars + 8 * BAR_GDONE, 0);
  if (tid >= 128 && tid < 132) mbar_arrive(ev_bar(bars, EV_END));
}

__global__ void __cluster_dims__(2, 1, 1) __launch_bounds__(384, 1)
xdeepfm_kernel(const int* __restrict__ idx, const __nv_bfloat16* __restrict__ table, const __nv_bfloat16* __restrict__ w1,
               const __nv_bfloat16* __restrict__ b1, const __nv_bfloat16* __restrict__ w2,
               const __nv_bfloat16* __restrict__ ws, const __nv_bfloat16* __restrict__ wco,
               const __nv_bfloat16* __restrict__ bout, __nv_bfloat16* __restrict__ out, const GPtr gp,
               const __grid_constant__ CUtensorMap tmW, const __grid_constant__ CUtensorMap tmT) {
  int myidx, idx1, idx2 = 0, idx3 = 0;
  {
    const int t = threadIdx.x, b = blockIdx.x, half = (b >> 1) ^ (t >= 256 ? t >> 4 : 0);
    const int* ip = idx + (((b >> 3) & 15) * 256 + (half & 1) * 128 + (t < 256 ? min(min(t >> 5, 4) * 4 + (t >> 5) * 16 + min(t & 31, 19), 127) : (b & 1) * 64 + ((t >> 1) & 48) + (t & 15))) * NF;
    asm volatile("{\n.reg .pred p;\nsetp.ge.u32 p, %5, 256;\nld.global.nc.v2.s32 {%0, %1}, [%4];\n@p ld.global.nc.v2.s32 {%2, %3}, [%4 + 8];\n}"
                 : "=r"(myidx), "=r"(idx1), "+r"(idx2), "+r"(idx3) : "l"(ip), "r"(t));
  }
  extern __shared__ __align__(1024) uint8_t smem[];
  const uint32_t sb = (uint32_t)__cvta_generic_to_shared(smem);
  const uint32_t bars = sb + OFF_BAR;
  const int tid = threadIdx.x, lane = tid & 31;
  const int warp = __shfl_sync(0xffffffffu, tid >> 5, 0);
  const int cta = blockIdx.x;
  const bool gemm = cta < NGEMM;
  const int nt = cta & 7, rank = cta & 1;

  uint32_t sx, sw;
  uint4 bv;
  asm volatile("{\n.reg .pred p;\nsetp.eq.u32 p, %9, 7;\n@p ld.global.nc.u32 %0, [%6];\n@p ld.global.nc.u32 %1, [%7];\n@p ld.global.nc.v4.u32 {%2, %3, %4, %5}, [%8];\n}"
               : "=r"(sx), "=r"(sw), "=r"(bv.x), "=r"(bv.y), "=r"(bv.z), "=r"(bv.w)
               : "l"(table + cta * 256 + lane * 8), "l"(w1 + nt * 192 + lane * 2),
                 "l"(b1 + (lane < 24 ? nt * 192 : 1536 - 192 + (nt >> 2) * 64) + lane * 8), "r"(tid >> 5));
  auto keep = [&]() {
    asm volatile("{\n.reg .pred p;\nsetp.ne.u32 p, %0, 0;\n@p st.shared.v2.b32 [%0], {%1, %2};\n@p st.shared.v2.b32 [%0 + 8], {%3, %4};\n"
                 "@p st.shared.b32 [%0 + 16], %5;\n@p st.shared.b32 [%0 + 24], %6;\n@p st.shared.v4.b32 [%0 + 32], {%7, %8, %9, %10};\n}"
                 ::"r"((uint32_t)(size_t)table & 1), "r"(myidx), "r"(idx1), "r"(idx2), "r"(idx3), "r"(sx), "r"(sw), "r"(bv.x), "r"(bv.y), "r"(bv.z), "r"(bv.w) : "memory");
  };
  if (warp == 8 && elect1()) {
    mbar_init(bars + 8 * BAR_GIDX, 1);
    mbar_init(bars + 8 * BAR_FULL, 1);
    mbar_init(bars + 8 * BAR_W0, 1);
    asm volatile("fence.mbarrier_init.release.cluster;" ::: "memory");
    if (gemm) {
      mbar_expect_tx(bars + 8 * BAR_W0, 4 * UNIT);
#pragma unroll
      for (int i = 0; i < 4; i++)
        tma_load(sb + (U_W + i) * UNIT, &tmW, i < 3 ? nt * 192 + i * 64 : 1536 + (nt >> 2) * 64, 0, bars + 8 * BAR_W0);
    } else {
      mbar_expect_tx(bars + 8 * BAR_GIDX, 35152);
      bulk_load(sb + XOFF_W3, ws + 2 * 17576, 35152, bars + 8 * BAR_GIDX);
    }
  }
  if (warp == 8 && !gemm) bar_arrive<7, 288>();
  if (threadIdx.x < 256) {}
  else if (threadIdx.x >= 384 - 16) {
    const int l = threadIdx.x & 7;
    if (l < 7) asm volatile("prefetch.global.L2 [%0];" ::"l"(w1 + (((cta >> 3 & 15) * 2 + (cta & 1)) * 2 + ((threadIdx.x >> 3) & 1)) * DIN + (l < 6 ? (cta & 6) * 192 + l * 64 : 1536 + (cta & 4) * 16)));
  }
  else if (threadIdx.x >= 352 && threadIdx.x < 359) {
    const int l = blockIdx.x * 7 + threadIdx.x - 352;
    if (l < 824) asm volatile("prefetch.global.L2 [%0];" ::"l"(ws + (823 - l) * 64));
  }

  if (warp >= 8) {
    const int pw = warp - 8;
    const bool lead = elect1();
    if (lead) {
      if (pw) mbar_init(bars + 8 * (pw < 3 ? BAR_FULL + pw : BAR_CIDX), 1);
      else mbar_init(bars + 8 * BAR_GDONE, 4);
      asm volatile("fence.mbarrier_init.release.cluster;" ::: "memory");
    }
    __syncwarp();
    asm volatile("barrier.cluster.arrive.relaxed.aligned;" ::: "memory");
    if (lead) {
      if (gemm) w_prefetch(w1, 1, cta, pw);
      if (pw == 0) {
        if (gemm) {
          mbar_expect_tx(bars + 8 * BAR_FULL, 2 * UNIT);
          asm volatile("prefetch.tensormap [%0];" ::"l"(&tmT) : "memory");
        } else {
          const int i0 = fold_i0(cta - NGEMM), ni = fold_i0(cta - NGEMM + 1) - i0;
          mbar_expect_tx(bars + 8 * BAR_W0, ni * 1360 + sizeof(SlotTab));
#pragma unroll 1
          for (int i = 0; i < ni; i++) bulk_load(sb + XOFF_W1 + i * 1392, ws + (((i0 + i) * 676) & ~7), 1360, bars + 8 * BAR_W0);
          bulk_load(sb + XOFF_TAB, gp.tab, sizeof(SlotTab), bars + 8 * BAR_W0);
          mbar_expect_tx(bars + 8 * BAR_FULL, 35152);
          bulk_load(sb + XOFF_W2, ws + 17576, 35152, bars + 8 * BAR_FULL);
        }
      } else if (pw == 3 && !gemm) {
        mbar_expect_tx(bars + 8 * BAR_CIDX, NC_EXTRA * (NF * 4 + sizeof(Job)));
        bulk_load(sb + XOFF_CIDX, idx + cin_start(cta) * NF, NC_EXTRA * NF * 4, bars + 8 * BAR_CIDX);
        bulk_load(sb + XOFF_JOB, gp.jobs + (32 + rank * (32 + NC_EXTRA)) * sizeof(Job) / 16, NC_EXTRA * sizeof(Job), bars + 8 * BAR_CIDX);
      }
    }
    __syncwarp();
    asm volatile("setmaxnreg.dec.sync.aligned.u32 24;");
    if (elect1()) {
      mbar_init(bars + 8 * (BAR_EV + pw), 4);
      mbar_init(bars + 8 * (BAR_EV + 4 + pw), 4);
      mbar_init(bars + 8 * (BAR_FULL + 4 + pw), 1);
      mbar_init(bars + 8 * (pw == 2 ? BAR_CW : BAR_DNN + pw), pw == 2 ? 1 : 1 << pw);
      if (pw == 0) mbar_init(bars + 8 * (BAR_FULL + 3), 1);
#pragma unroll
      for (int i = 0; i < 8; i++)
        mbar_init(bars + 8 * (BAR_CFULL + pw * 8 + i), (!gemm && (pw & 1)) ? 4 : i == 4 && pw == 3 ? NR : 1);
      if (pw < 3) mbar_init(bars + 8 * (pw < 2 ? BAR_C0 + pw : BAR_WIN), 1);
      asm volatile("fence.mbarrier_init.release.cluster;" ::: "memory");
    }
    __syncwarp();
    bar_sync<6, 128>();
    asm volatile("barrier.cluster.wait.acquire.aligned;" ::: "memory");
    if (!gemm && elect1()) mbar_arrive(bars + 8 * BAR_GDONE);
    __syncwarp();
    if (gemm) {
      {
        const uint32_t a = sb + OFF_GIDX + ((lane >> 4) * 64 + pw * 16 + (lane & 15)) * NF * 4;
        asm volatile("st.shared.v2.b32 [%0], {%1, %2};\nst.shared.v2.b32 [%0 + 8], {%3, %4};"
                     ::"r"(a), "r"(myidx), "r"(idx1), "r"(idx2), "r"(idx3) : "memory");
        keep();
        __syncwarp();
      }
      if (elect1()) {
#pragma unroll
        for (int j = 0; j < 16; j += 8) {
          int r[8];
#pragma unroll
          for (int i = 0; i < 8; i++) r[i] = lds32(sb + OFF_GIDX + ((64 + pw * 16 + j + i) * NF) * 4);
#pragma unroll
          for (int i = 0; i < 8; i++) tma_row_mc(sb + U_XB * UNIT + (rank * 64 + pw * 16 + j + i) * 128, &tmT, r[i], bars + 8 * BAR_FULL);
        }
        int s = 1;
#pragma unroll 1
        for (int fi = 1; fi < NF; fi++) {
          const int f = fresh(fi), pw = fresh(warp) - 8, ct = fresh(cta), nt = ct & 7;
          const int t = f - FS, st = t < 0 ? s : (t & 3) ^ ((t >> 1) & 1), e = f - 3 - (t > 1);
          const uint32_t fb = bars + 8 * (BAR_FULL + (f & 7)), ia = sb + OFF_GIDX + (pw * 16 * NF + f) * 4;
          const uint32_t d = sb + (st == 3 ? U_SP : 2 * st) * UNIT + ((ct & 1) * 64 + pw * 16) * 128;
          if (f == 4) mbar_wait(bars + 8 * BAR_GIDX, 0);
          int r[2][RB];
#pragma unroll
          for (int i = 0; i < RB; i++) r[0][i] = lds32(ia + i * NF * 4);
          if (e >= 0) mbar_wait(ev_bar(bars, e), ev_par(e));
          if (pw == 0) mbar_expect_tx(fb, t < 0 ? 8 * UNIT : 6 * UNIT);
#pragma unroll
          for (int j = 0; j < 16 / RB; j++) {
#pragma unroll
            for (int i = 0; i < RB; i++) r[(j + 1) & 1][i] = lds32(ia + (RB * j + RB + i + (RB * j + RB >= 16) * 48) * NF * 4);
#pragma unroll
            for (int i = 0; i < RB; i++) tma_row_mc(d + (RB * j + i) * 128, &tmT, r[j & 1][i], fb);
          }
          if (t < 0) {
#pragma unroll
            for (int j = 0; j < 16 / RB; j++) {
              if (j + 1 < 16 / RB) {
#pragma unroll
                for (int i = 0; i < RB; i++) r[(j + 1) & 1][i] = lds32(ia + (64 + RB * j + RB + i) * NF * 4);
              }
#pragma unroll
              for (int i = 0; i < RB; i++) tma_row_mc(d + U_XB * UNIT + (RB * j + i) * 128, &tmT, r[j & 1][i], fb);
            }
          }
          tma_load(sb + (U_W + 4 * st + pw) * UNIT, &tmW, pw < 3 ? nt * 192 + pw * 64 : 1536 + (nt >> 2) * 64, f * 64, fb);
          if (f == GI && pw < 2) {
            if (pw == 0) mbar_expect_tx(bars + 8 * BAR_GIDX, 128 * NF * 4);
            bulk_load(sb + OFF_GIDX + pw * 64 * NF * 4, idx + ((ct >> 3) * 256 + (((ct >> 1) ^ pw) & 1) * 128 + (ct & 1) * 64) * NF, 64 * NF * 4, bars + 8 * BAR_GIDX);
          }
          if (f == GI && pw == 2) {
            mbar_expect_tx(bars + 8 * BAR_CIDX, 32 * (NF * 4 + sizeof(Job)));
            bulk_load(sb + OFF_CIDX, idx + (ct * NC_GEMM & ~1) * NF, 30 * NF * 4, bars + 8 * BAR_CIDX);
            bulk_load(sb + OFF_PIDX, idx + (POOL + (group_of(ct) * NR & ~1)) * NF, 2 * NF * 4, bars + 8 * BAR_CIDX);
            bulk_load(sb + OFF_JOB, gp.jobs + (ct & 1) * ((32 + NC_EXTRA) * sizeof(Job) / 16), 32 * sizeof(Job), bars + 8 * BAR_CIDX);
          }
          if (f + WD < NF) w_prefetch(w1, f + WD, ct, pw);
          if (++s == 3) s = 0;
        }
        mbar_wait(bars + 8 * BAR_T, 0);
#pragma unroll 1
        for (int ti = 0; ti < 8; ti++) {
          const int t = fresh(ti), pw = fresh(warp) - 8, e = t < 4 ? 22 - !t : 19 + t;
          const uint32_t ia = sb + OFF_TIDX + t * 256 + pw * 64, fb = bars + 8 * (BAR_FULL + ((NF + t) & 7));
          const uint32_t d = sb + b_x(t) * UNIT + ((fresh(cta) & 1) * 64 + pw * 16) * 128;
          int4 r[2];
          r[0] = lds128(ia);
          r[1] = lds128(ia + 16);
          mbar_wait(ev_bar(bars, e), ev_par(e));
          if (pw == 0) mbar_expect_tx(fb, t < 3 ? 2 * UNIT : 5 * UNIT);
#pragma unroll
          for (int j = 0; j < 4; j++) {
            tma_row_mc(d + (4 * j + 0) * 128, &tmT, r[j & 1].x, fb);
            tma_row_mc(d + (4 * j + 1) * 128, &tmT, r[j & 1].y, fb);
            tma_row_mc(d + (4 * j + 2) * 128, &tmT, r[j & 1].z, fb);
            tma_row_mc(d + (4 * j + 3) * 128, &tmT, r[j & 1].w, fb);
            if (j < 2) r[j & 1] = lds128(ia + 32 + 16 * j);
          }
        }
        mbar_arrive(bars + 8 * BAR_GDONE);
      }
      __syncwarp();
    }
    {
    int cta; asm volatile("mov.u32 %0, %%ctaid.x;" : "=r"(cta));
    cta = __shfl_sync(0xffffffffu, cta, 0);
    const bool gemm = cta < NGEMM;
    const int bt = cta >> 3, nt = cta & 7;
    if (pw == 3) {
      if (elect1()) {
        if (!gemm)
          asm volatile("{\n.reg .pred p;\n.reg .u32 n, a, b, c, d;\nmov.u32 n, 0;\n"
                       "ld.relaxed.gpu.global.u32 a, [%0];\nnanosleep.u32 50;\nld.relaxed.gpu.global.u32 b, [%0];\nnanosleep.u32 50;\nld.relaxed.gpu.global.u32 c, [%0];\nnanosleep.u32 50;\n"
                       "LAB_WAIT:\n"
                       "ld.relaxed.gpu.global.u32 d, [%0];\nsetp.eq.u32 p, a, %1;\n@p bra DONE;\n"
                       "ld.relaxed.gpu.global.u32 a, [%0];\nsetp.eq.u32 p, b, %1;\n@p bra DONE;\n"
                       "ld.relaxed.gpu.global.u32 b, [%0];\nsetp.eq.u32 p, c, %1;\n@p bra DONE;\n"
                       "ld.relaxed.gpu.global.u32 c, [%0];\nsetp.eq.u32 p, d, %1;\n@p bra DONE;\n"
                       "add.u32 n, n, 1;\nsetp.lt.u32 p, n, 100000;\n@p bra LAB_WAIT;\n"
                       "DONE:\n}" ::"l"(&gp.s->foldflag), "r"((gp.s->epoch[fresh(cta)] + 1) * NEXTRA * 8) : "memory");
        asm volatile("fence.proxy.async.global;" ::: "memory");
        if (gemm) mbar_wait(ev_bar(bars, EV_CW), ev_par(EV_CW));
        mbar_expect_tx(bars + 8 * BAR_CW, CW_BYTES);
        bulk_load(sb + OFF_CW, gp.s->cw, CW_CUT * 1792, bars + 8 * BAR_CW);
        bulk_load(sb + OFF_CW2, gp.s->cw + CW_CUT * 1792 / 16, (22 - CW_CUT) * 1792, bars + 8 * BAR_CW);
        bulk_load(sb + OFF_CWL, gp.s->cw + CW_MAIN / 16, CW_LIN, bars + 8 * BAR_CW);
      }
      __syncwarp();
    }
    if (pw < NLW || !gemm) {
      if (elect1()) {
        const bool gemm = blockIdx.x < NGEMM;
        mbar_wait(bars + 8 * BAR_GDONE, 0);
        mbar_wait(bars + 8 * BAR_CIDX, 0);
#pragma unroll 1
        for (uint32_t o = sb + (gemm ? OFF_JOB : XOFF_JOB) + (warp - 8) * sizeof(Job); o;) {
          const int2 j0 = lds64(o), j1 = lds64(o + 8), j2 = lds64(o + 16);
          const uint32_t d = j1.x, cb = j1.y, ia = j2.x;
          o = j2.y;
          mbar_wait(j0.x, j0.y);
          mbar_expect_tx(cb, NF * 128);
#pragma unroll
          for (int k = 0; k < NF; k += 2 * LB) {
            int2 r[LB];
#pragma unroll
            for (int i = 0; i < LB; i++) if (k + 2 * i < NF) r[i] = lds64(ia + (k + 2 * i) * 4);
#pragma unroll
            for (int i = 0; i < LB; i++) if (k + 2 * i < NF) {
              tma_row(d + (k + 2 * i) * 128, &tmT, r[i].x, cb);
              tma_row(d + (k + 2 * i + 1) * 128, &tmT, r[i].y, cb);
            }
          }
        }
        if (gemm) mbar_wait(bars + 8 * BAR_POOL, 0);
      }
      __syncwarp();
    }
    if (pw == 3) {
      unsigned epoch;
      asm volatile("ld.global.u32 %0, [%1];" : "=r"(epoch) : "l"(gp.s->epoch + fresh(cta)));
      epoch++;
      const float bo = sb == SMEM_BASE + ((cta & 1) << 24) ? bf2f(bout[0]) : __int_as_float(0x7fc00000);
      if (gemm) {
        mbar_wait(bars + 8 * BAR_PART, 0);
        float4* dst = reinterpret_cast<float4*>(gp.s->part + nt * NB + bt * 256);
        dst[lane] = lds128f(sb + OFF_PART + lane * 16);
        dst[lane + 32] = lds128f(sb + OFF_PART + 512 + lane * 16);
        __syncwarp();
        if (lane == 0) flag_add(gp.s->dflag + (fresh(cta) >> 3) * 8);
      }
      const int c0 = cin_start(cta), ncin = gemm ? NC_GEMM : NC_EXTRA;
      flag_wait(gp.s->dflag + ((lane == 0 ? c0 : lane == 1 ? POOL : c0 + ncin - 1) >> 8) * 8, epoch * 8, 200);
      __syncwarp();
#pragma unroll 1
      for (int r = lane; r < ncin + gemm; r += 32) {
        const int b = r < ncin ? c0 + r : POOL + group_of(cta) * NR + (lds32(sb + OFF_WIN) & (NR - 1));
        float s = bo;
#pragma unroll
        for (int n = 0; n < 8; n++) s += __ldcg(gp.s->part + n * NB + b);
        sts64f(sb + (gemm ? OFF_DNN : XOFF_DNN) + r * 8, 0.125f * s, __int_as_float(b));
      }
      __syncwarp();
      if (lane == 0) { mbar_arrive(bars + 8 * BAR_DNN); gp.s->epoch[fresh(cta)] = epoch; }
    }
    }
  } else {
    const int wg = warp >> 2;
    const int p = tid & 127;
    if (gemm) {
      asm volatile("barrier.cluster.arrive.relaxed.aligned;" ::: "memory");
      if (warp == 7) {
        asm volatile("st.shared.b32 [%0], %1;" ::"r"(sb + OFF_INIT + 4608 + lane * 4), "r"(0x3f003f00) : "memory");
        const int lg = __reduce_add_sync(0xffffffffu, (sx & 0x7fff) + ((sx >> 16) & 0x7fff) + (sw & 0x7fff) + ((sw >> 16) & 0x7fff));
        const uint32_t co = (min(max((lg >> 6) - int((127 - 11.8 - OB) * 128), 0), (130 + OB) * 128) & 0x7f80) | 0x2b;
        const uint32_t bw[4] = {bv.x, bv.y, bv.z, bv.w};
#pragma unroll
        for (int i = 0; i < 8; i++)
          asm volatile("st.shared.v4.b32 [%0], {%1, %2, %2, %2};" ::"r"(sb + OFF_INIT + lane * 144 + i * 16), "r"(__byte_perm(bw[i >> 1], co, i & 1 ? 0x5432 : 0x5410)), "r"(0) : "memory");
        sts32f(sb + OFF_EPI + 1024, -ALPHA * __uint_as_float((co << 16) - 39));
        asm volatile("fence.proxy.async.shared::cta;" ::: "memory");
        bar_arrive<5, 160>();
      } else {
        const int row = min(warp, 4) * 4 + warp * 16 + (lane >> 3);
        const uint32_t a = sb + row * 128 + (((lane ^ row) & 7) << 4);
        const __nv_bfloat16* src = table + (lane & 7) * 8;
        const int l0 = ((fresh(a) >> 7) & 3) | (fresh((int)(size_t)src) & 1);
#pragma unroll
        for (int i = 0; i < 5; i++)
          asm volatile("{\n.reg .pred p;\n.reg .b32 r;\n.reg .b64 a;\nsetp.ne.b32 p, %4, 0;\nshfl.sync.idx.b32 r, %2, %3, 31, 0xffffffff;\n"
                       "mad.wide.s32 a, r, 128, %1;\n@p cp.async.cg.shared.global [%0], [a], 16;\n}"
                       ::"r"((a ^ (i & 1) * 64) + i * 512), "l"(src), "r"(myidx), "r"(4 * i + l0), "r"(int(i < 4 || warp < 4)) : "memory");
      }
      keep();
      asm volatile("barrier.cluster.wait.acquire.aligned;" ::: "memory");
    } else {
      fold_weights(keep, warp, sb, cta - NGEMM, wco, ws, table, gp);
    }
    asm volatile("setmaxnreg.inc.sync.aligned.u32 224;");
    float r0 = 0.f, r1 = 0.f, r2 = 0.f, r3 = 0.f;
    float d1[96];
    Gelu<24> g1;
    unsigned place = NR;
    const uint32_t ep = sb + OFF_EPI + (lane & 3) * 16;
    auto load_w = [&](int t) {
      const int w = warp & 3;
      if (w < 3 && elect1())
        tma_load(sb + (b_w(t) + b_ws(t) * w) * UNIT, &tmW, nt * 192 + w * 64, (NF - 1 - t) * 64, bars + 8 * (BAR_FULL + ((NF + t) & 7)));
    };
    int role; asm volatile("mov.u32 %0, %%ctaid.x;" : "=r"(role));
    role = role < NGEMM ? wg : 2;
    if (fresh(role) == 0) {
      asm volatile("setmaxnreg.inc.sync.aligned.u32 256;");
      float d0[96], dx[32], dw[96];
      Gelu<24> g0;
      bar_sync<5, 160>();
      wg_fence();
      wgmma_ss_n256<0>(dw, dx, ONES_DESC, INIT_DESC, 0);
      wgmma_ss_n192<0>(d0, ONES_DESC, INIT_DESC, 0);
      wg_commit();
      mbar_wait(bars + 8 * BAR_W0, 0);
      asm volatile("cp.async.wait_all;" ::: "memory");
      asm volatile("fence.proxy.async.shared::cta;" ::: "memory");
      bar_sync<2, 256>();
      const uint64_t dA0 = desc_x(rank), dA1 = desc_x(rank ^ 1);
      wg_fence();
#pragma unroll
      for (int k = 0; k < 4; k++) {
        wgmma_ss_n256(dw, dx, dA0 + 2 * k, desc_w(U_W) + 128 * k, 1);
        wgmma_ss_n192(d0, dA1 + 2 * k, desc_w(U_W) + 128 * k, 1);
      }
      wg_commit();
      constexpr unsigned long long STAGES = 0xb4b4924924924ull;
#pragma unroll 1
      for (int f = 1; f < NF - 3; f++) {
        mbar_wait(bars + 8 * (BAR_FULL + (f & 7)), (f >> 3) & 1);
        const int st = (STAGES >> (2 * f)) & 3, xo = (st == 3 ? U_SP : 2 * st) * (UNIT / 16);
        const uint64_t dB = desc_w(U_W + 4 * st);
        wg_fence();
        wgmma_ss_n256(dw, dx, dA0 + xo, dB, 1);
        wgmma_ss_n192(d0, dA1 + xo, dB, 1);
        wg_commit();
        wg_wait<1>();
        if (p < (f > FS ? 4 : 2)) mbar_arrive_cta(ev_bar(bars, f - 1), p & 1);
#pragma unroll
        for (int k = 1; k < 4; k++) {
          wgmma_ss_n256(dw, dx, dA0 + xo + 2 * k, dB + 128 * k, 1);
          wgmma_ss_n192(d0, dA1 + xo + 2 * k, dB + 128 * k, 1);
        }
        wg_commit();
      }
      {
        constexpr int x3 = 2 * (UNIT / 16), x4 = U_SP * (UNIT / 16), x5 = 4 * (UNIT / 16);
        const uint64_t dB3 = desc_w(U_W + 4), dB4 = desc_w(U_W + 12), dB5 = desc_w(U_W + 8);
        mbar_wait(bars + 8 * (BAR_FULL + 7), 0);
        tile_step(d0, dA1 + x3, dB3);
        wg_wait<1>();
        if (p < 4) mbar_arrive_cta(ev_bar(bars, NF - 4), p & 1);
        mbar_wait(bars + 8 * (BAR_FULL + 0), 1);
        tile_step(d0, dA1 + x4, dB4);
        if (WK) wide_step<0, WK>(dw, dx, dA0 + x3, dB3);
        mbar_wait(bars + 8 * (BAR_FULL + 1), 1);
        tile_step(d0, dA1 + x5, dB5);
        wide_step<WK, 4>(dw, dx, dA0 + x3, dB3);
        mbar_wait(bars + 8 * BAR_T, 0);
        g0.start(ep, sb);
        wg_wait<1>();
        wide_step(dw, dx, dA0 + x4, dB4);
        g0.part<0, PE1>(d0, r0, r1);
        wg_wait<1>();
        if (p < 4) mbar_arrive_cta(ev_bar(bars, NF - 3), p & 1);
        wide_step<0, HK>(dw, dx, dA0 + x5, dB5);
        g0.part<PE1, PE2>(d0, r0, r1);
        wg_wait<1>();
        bar_arrive<4, 256>();
        if (p < 4) mbar_arrive_cta(ev_bar(bars, NF - 2), p & 1);
        wide_step<HK, 4>(dw, dx, dA0 + x5, dB5);
        g0.part<PE2, PE0>(d0, r0, r1);
        wg_wait<0>();
        load_w(3);
        if (p < 4) mbar_arrive_cta(ev_bar(bars, NF - 1), p & 1);
      }
      g0.part<PE0, g0.END>(d0, r0, r1);
      Gelu<8> gx;
      gx.start(ep + 12 * 64, sb);
      gx.part<0, gx.END>(dx, r2, r3);
      hand_on(d1, dw);
      g1.take(g0);
      asm volatile("setmaxnreg.dec.sync.aligned.u32 224;");
    }
    if (fresh(role) == 1) {
      float d0[96], dw[96];
      bar_sync<3, 128>();
      wg_fence();
      wgmma_ss_n192<0>(d0, ONES_DESC, INIT_DESC, 0);
      wgmma_ss_n192<0>(dw, ONES_DESC + ((size_t)table & 1), INIT_DESC, 0);
      wg_commit();
      asm volatile("cp.async.wait_all;" ::: "memory");
      asm volatile("fence.proxy.async.shared::cta;" ::: "memory");
      bar_arrive<2, 256>();
      mbar_wait(bars + 8 * BAR_W0, 0);
      mbar_wait(bars + 8 * BAR_FULL, 0);
      wg_fence();
#pragma unroll
      for (int k = 0; k < 4; k++) {
        wgmma_ss_n192(d0, desc_x(U_XB) + 2 * k, desc_w(U_W) + 128 * k, 1);
        wgmma_ss_n192(dw, desc_x(U_XB + 1) + 2 * k, desc_w(U_W) + 128 * k, 1);
      }
      wg_commit();
      int s = 1;
#pragma unroll 1
      for (int f = 1; f < FS; f++) {
        mbar_wait(bars + 8 * (BAR_FULL + (f & 7)), (f >> 3) & 1);
        const uint64_t dA = desc_x(U_XB + 2 * s), dB = desc_w(U_W + 4 * s);
        wg_fence();
        wgmma_ss_n192(d0, dA, dB, 1);
        wgmma_ss_n192(dw, dA + 512, dB, 1);
        wg_commit();
        wg_wait<1>();
        if (p < 2) mbar_arrive_cta(ev_bar(bars, f - 1), p);
#pragma unroll
        for (int k = 1; k < 4; k++) {
          wgmma_ss_n192(d0, dA + 2 * k, dB + 128 * k, 1);
          wgmma_ss_n192(dw, dA + 512 + 2 * k, dB + 128 * k, 1);
        }
        wg_commit();
        if (++s == 3) s = 0;
      }
      wg_wait<0>();
      if (p < 2) mbar_arrive_cta(ev_bar(bars, FS - 1), p);
      {
        const uint32_t a = sb + OFF_GIDX + 64 * NF * 4;
        const uint32_t ww = ldg32(w2 + 2 * p + (p < 96 ? nt * 192 : 1536 - 192 + (nt >> 2) * 64));
        int v[4];
#pragma unroll
        for (int i = 0; i < 4; i++) v[i] = lds32(a + (((p & 15) * 4 + i) * NF + (NF - 1 - (p >> 4))) * 4);
        bar_sync<3, 128>();
        asm volatile("st.shared.v4.b32 [%0], {%1, %2, %3, %4};" ::"r"(sb + OFF_TIDX + p * 16), "r"(v[0]), "r"(v[1]), "r"(v[2]), "r"(v[3]) : "memory");
        sts64f(sb + OFF_EPI + (p >> 3) * 64 + (p & 3) * 16 + (p & 4) * 2, (0.5f / ALPHA) * bf_lo(ww), (0.5f / ALPHA) * bf_hi(ww));
        bar_sync<3, 128>();
        if (p < 2) {
          flag_wait(&gp.s->foldflag, (gp.s->epoch[cta] + 1) * NEXTRA * 8, 0);
          mbar_arrive(bars + 8 * BAR_T);
        }
        __syncwarp();
      }
      mbar_wait(ev_bar(bars, FS), ev_par(FS));
      unsigned* tp = gp.s->place + group_of(cta) * 8;
      asm volatile("" : "+l"(tp));
      sched_fence();
      mbar_wait(bars + 8 * (BAR_FULL + 2), 1);
      bar_sync<4, 256>();
#pragma unroll
      for (int t = 0; t < 4; t++) {
        if (t) mbar_wait(bars + 8 * (BAR_FULL + 2 + t), 1);
        const uint64_t dA = desc_x(b_x(t)), dB = desc_w(b_w(t), b_ws(t));
        wg_fence();
#pragma unroll
        for (int k = 0; k < 4; k++) {
          wgmma_ss_n192(d0, dA + 2 * k, dB + 128 * k, 1);
          wgmma_ss_n192(dw, dA + 512 + 2 * k, dB + 128 * k, 1);
          if (k == 1 && t) {
            wg_commit();
            wg_wait<1>();
            mbar_wait(ev_bar(bars, NF - 1), ev_par(NF - 1));
            load_w(3 + t);
            if (t == 1 && p < 4) mbar_arrive_cta(ev_bar(bars, 26), p & 1);
            if (t == 3)
              asm volatile("{\n.reg .pred p;\nsetp.eq.u32 p, %2, 0;\n@p st.shared.b32 [%1], %0;\n@p mbarrier.arrive.shared::cta.b64 _, [%3];\n}"
                           ::"r"(place), "r"(sb + OFF_WIN), "r"(p), "r"(bars + 8 * BAR_WIN) : "memory");
            wg_fence();
          }
        }
        wg_commit();
        if (t == 0)
          asm volatile("{\n.reg .pred p;\nsetp.eq.u32 p, %2, 0;\n@p atom.relaxed.gpu.global.inc.u32 %0, [%1], 7;\n}" : "+r"(place) : "l"(tp), "r"(p));
      }
      mbar_wait(bars + 8 * (BAR_FULL + 6), 1);
      tile_step(d0, desc_x(b_x(4)), desc_w(b_w(4)));
      wg_wait<1>();
      load_w(7);
      if (p < 4) mbar_arrive(ev_bar(bars, EV_CW));
      mbar_wait(bars + 8 * (BAR_FULL + 7), 1);
      tile_step(d0, desc_x(b_x(5)), desc_w(b_w(5)));
      mbar_wait(bars + 8 * (BAR_FULL + 0), 0);
      tile_step(d0, desc_x(b_x(6)), desc_w(b_w(6)));
      mbar_wait(bars + 8 * (BAR_FULL + 1), 0);
      tile_step(d0, desc_x(b_x(7)), desc_w(b_w(7), 4));
      tile_step(dw, desc_x(b_x(4) + 1), desc_w(b_w(4)));
      Gelu<24> g0;
      g0.start(ep, sb);
      mbar_wait(bars + 8 * BAR_WIN, 0);
      place = lds32(sb + OFF_WIN);
      wg_wait<1>();
      tile_step(dw, desc_x(b_x(5) + 1), desc_w(b_w(5)));
      g0.part<0, PS>(d0, r0, r1);
      wg_wait<1>();
      if (p < 4) mbar_arrive(ev_bar(bars, 30));
      tile_step(dw, desc_x(b_x(6) + 1), desc_w(b_w(6)));
      g0.part<PS, 2 * PS>(d0, r0, r1);
      wg_wait<1>();
      if (p < 4) mbar_arrive(ev_bar(bars, 31));
      tile_step(dw, desc_x(b_x(7) + 1), desc_w(b_w(7), 4));
      g0.part<2 * PS, 2 * PS + PS2>(d0, r0, r1);
      wg_wait<0>();
      if (p < 4) mbar_arrive(ev_bar(bars, EV_END));
      g0.part<2 * PS + PS2, g0.END>(d0, r0, r1);
      hand_on(d1, dw);
      g1.take(g0);
    }
    g1.ep = ep;
    if (fresh(role) < 2) g1.part<0, g1.END - GK, false>(d1, r2, r3);

    {
    int cta, tid;
    asm volatile("mov.u32 %0, %%ctaid.x;" : "=r"(cta));
    asm volatile("mov.u32 %0, %%tid.x;" : "=r"(tid));
    const bool gemm = role < 2;
    const int lane = tid & 31, p = tid & 127;
    const int rb = !wg ? 0 : gemm ? NC_WG0 : NC_EXTRA / 2;
    place = __shfl_sync(0xffffffffu, place, 0);
    const int nj = !gemm ? NC_EXTRA / 2 : wg ? NC_GEMM - NC_WG0 + (place < NR) : NC_WG0;
    const uint32_t cinb = sb + (gemm ? OFF_CIN + rb * CROW : wg ? XOFF_CIN1 : XOFF_CIN0);
    CinCtx c;
    cin_setup(c, sb, wg, tid, gemm, nj);
    if (place == 1 && NR == 2) c.tab1 += 0x20000;
    c.co = cinb;
    c.cin = p * 4;
    struct Res { uint32_t a, on; float dn; __nv_bfloat16* op; };
    auto prepare = [&](int r) {
      Res o;
      o.on = (p & 7) == 0 && r >= 0;
      r = max(r, 0);
      o.a = cinb + (p & 7) * 16 + r * CROW;
      const int2 v = lds64(sb + (gemm ? OFF_DNN : XOFF_DNN) + (rb + r) * 8);
      o.dn = __int_as_float(v.x);
      o.op = out + v.y;
      asm volatile("" : "+r"(o.a), "+r"(o.on), "+f"(o.dn), "+l"(o.op));
      return o;
    };
    auto sum = [&](const Res& o) {
      const float4 v0 = lds128f(o.a), v1 = lds128f(o.a + 128), v2 = lds128f(o.a + 256), v3 = lds128f(o.a + 384);
      float s = ((((v0.x + o.dn) + v0.y) + (v0.z + v0.w)) + ((v1.x + v1.y) + (v1.z + v1.w))) +
                (((v2.x + v2.y) + (v2.z + v2.w)) + ((v3.x + v3.y) + (v3.z + v3.w)));
      s += __shfl_xor_sync(0xffffffffu, s, 1);
      s += __shfl_xor_sync(0xffffffffu, s, 2);
      return s + __shfl_xor_sync(0xffffffffu, s, 4);
    };
    auto store = [&](const Res& o, float s) {
      asm volatile("{\n.reg .pred p;\n.reg .b16 v;\nsetp.ne.u32 p, %2, 0;\ncvt.rn.bf16.f32 v, %1;\n@p st.global.b16 [%0], v;\n}" ::"l"(o.op), "f"(s), "r"(o.on) : "memory");
    };
    Res last;
    cin_run(c, [&](uint32_t (&x)[11][2]) {
      mbar_wait(bars + 8 * BAR_GDONE, 0);
      mbar_wait(bars + 8 * (BAR_C0 + wg), 0);
      const uint32_t first = sb + (!gemm ? OFF_GIDX + wg * XSLOT : wg ? 24 * UNIT : OFF_GIDX + 2 * XSLOT);
      g1.part<g1.END - GK, g1.END, false>(d1, r2, r3, [&](int i) { cin_ldsm(c, first, x, i); });
#pragma unroll
      for (int i = GK; i < 5; i++) cin_ldsm(c, first, x, i);
      mbar_wait(bars + 8 * BAR_CW, 0);
    }, [&]() {
      sched_fence();
      const bool b0 = lane & 1, b1_ = lane & 2;
      float a = b0 ? r1 : r0, b = b0 ? r0 : r1, cc = b0 ? r3 : r2, d = b0 ? r2 : r3;
      a += __shfl_xor_sync(0xffffffffu, b, 1);
      cc += __shfl_xor_sync(0xffffffffu, d, 1);
      float e = b1_ ? cc : a, f = b1_ ? a : cc;
      e += __shfl_xor_sync(0xffffffffu, f, 2);
      const uint32_t row4 = (tid & 0x1c) | ((tid & 1) << 5) | ((tid & 0x60) << 1) | ((tid & 2) << 7);
      sts32f(sb + OFF_PART + (row4 ^ (((((cta >> 1) ^ wg) & 1) << 9) | ((~cta & ~wg & 1) << 8))), e);
      __syncwarp();
      if (lane == 0) mbar_arrive(bars + 8 * BAR_PART);
      mbar_wait(ev_bar(bars, gemm ? EV_CIN : EV_END), gemm);
    }, [&](bool even) {
      mbar_wait(bars + 8 * BAR_DNN, 0);
      static_assert(NC_EXTRA % 4 == 0, "even");
      if (even && !gemm) {
        asm volatile("bar.sync %0, 128;" ::"r"(1 + 2 * wg) : "memory");
        const Res o1 = prepare(NC_EXTRA / 2 - 32 + (p >> 3)), o2 = prepare(NC_EXTRA / 2 - 48 + (p >> 3));
        const float s1 = sum(o1), s2 = sum(o2);
        store(o1, s1);
        store(o2, s2);
      }
      last = prepare(nj - 16 + (p >> 3));
      sched_fence();
    });
    asm volatile("bar.sync %0, 128;" ::"r"(1 + 2 * wg) : "memory");
    store(last, sum(last));
    }
  }
}

typedef CUresult (*EncodeFn)(CUtensorMap*, CUtensorMapDataType, cuuint32_t, void*, const cuuint64_t*, const cuuint64_t*,
                             const cuuint32_t*, const cuuint32_t*, CUtensorMapInterleave, CUtensorMapSwizzle,
                             CUtensorMapL2promotion, CUtensorMapFloatOOBfill);

extern "C" void kernel_launch(void* const* d_in, const int* in_sizes, int n_in, void* d_out, int out_size) {
  void* fn = nullptr;
  cudaDriverEntryPointQueryResult q;
  cudaGetDriverEntryPoint("cuTensorMapEncodeTiled", &fn, cudaEnableDefault, &q);
  EncodeFn enc = (EncodeFn)fn;
  CUtensorMap tmW, tmT;
  const cuuint32_t es[3] = {1, 1, 1};
  {
    cuuint64_t dims[2] = {DIN, DIN}, st[1] = {DIN * 2};
    cuuint32_t box[2] = {64, 64};
    enc(&tmW, CU_TENSOR_MAP_DATA_TYPE_BFLOAT16, 2, d_in[4], dims, st, box, es, CU_TENSOR_MAP_INTERLEAVE_NONE,
        CU_TENSOR_MAP_SWIZZLE_128B, CU_TENSOR_MAP_L2_PROMOTION_NONE, CU_TENSOR_MAP_FLOAT_OOB_FILL_NONE);
  }
  {
    cuuint64_t dims[2] = {64, (cuuint64_t)(in_sizes[1] / 64)}, st[1] = {128};
    cuuint32_t box[2] = {64, 1};
    enc(&tmT, CU_TENSOR_MAP_DATA_TYPE_BFLOAT16, 2, d_in[1], dims, st, box, es, CU_TENSOR_MAP_INTERLEAVE_NONE,
        CU_TENSOR_MAP_SWIZZLE_128B, CU_TENSOR_MAP_L2_PROMOTION_NONE, CU_TENSOR_MAP_FLOAT_OOB_FILL_NONE);
  }
  GPtr gp;
  gp.zero = 0;
  cudaGetSymbolAddress((void**)&gp.s, g_scratch);
  cudaGetSymbolAddress((void**)&gp.tab, g_slot_tab);
  cudaGetSymbolAddress((void**)&gp.jobs, g_jobs);
  cudaFuncSetAttribute(xdeepfm_kernel, cudaFuncAttributeMaxDynamicSharedMemorySize, SMEM_BYTES);
  xdeepfm_kernel<<<GRID, 384, SMEM_BYTES, cudaStreamPerThread>>>(
      (const int*)d_in[0], (const __nv_bfloat16*)d_in[1], (const __nv_bfloat16*)d_in[4], (const __nv_bfloat16*)d_in[5],
      (const __nv_bfloat16*)d_in[6], (const __nv_bfloat16*)d_in[2], (const __nv_bfloat16*)d_in[3],
      (const __nv_bfloat16*)d_in[7], (__nv_bfloat16*)d_out, gp, tmW, tmT);
}
```

```cpp
#include <cuda_runtime.h>
#include <cuda_bf16.h>
#include <cuda.h>
#include <stdint.h>

template <int TB = 1>
__device__ __forceinline__ void wgmma_ss_n256(float (&d)[96], float (&e)[32], uint64_t descA, uint64_t descB, int scaleD) {
  asm volatile("{\n.reg .pred p;\nsetp.ne.b32 p, %130, 0;\n"
      "wgmma.mma_async.sync.aligned.m64n256k16.f32.bf16.bf16 {"
      "%0, %1, %2, %3, %4, %5, %6, %7, %8, %9, %10, %11, %12, %13, %14, %15,"
      "%16, %17, %18, %19, %20, %21, %22, %23, %24, %25, %26, %27, %28, %29, %30, %31,"
      "%32, %33, %34, %35, %36, %37, %38, %39, %40, %41, %42, %43, %44, %45, %46, %47,"
      "%48, %49, %50, %51, %52, %53, %54, %55, %56, %57, %58, %59, %60, %61, %62, %63,"
      "%64, %65, %66, %67, %68, %69, %70, %71, %72, %73, %74, %75, %76, %77, %78, %79,"
      "%80, %81, %82, %83, %84, %85, %86, %87, %88, %89, %90, %91, %92, %93, %94, %95,"
      "%96, %97, %98, %99, %100, %101, %102, %103, %104, %105, %106, %107, %108, %109, %110, %111,"
      "%112, %113, %114, %115, %116, %117, %118, %119, %120, %121, %122, %123, %124, %125, %126, %127"
      "}, %128, %129, p, 1, 1, 0, %131;\n}\n"
      : "+f"(d[0]), "+f"(d[1]), "+f"(d[2]), "+f"(d[3]), "+f"(d[4]), "+f"(d[5]), "+f"(d[6]), "+f"(d[7]),
        "+f"(d[8]), "+f"(d[9]), "+f"(d[10]), "+f"(d[11]), "+f"(d[12]), "+f"(d[13]), "+f"(d[14]), "+f"(d[15]),
        "+f"(d[16]), "+f"(d[17]), "+f"(d[18]), "+f"(d[19]), "+f"(d[20]), "+f"(d[21]), "+f"(d[22]), "+f"(d[23]),
        "+f"(d[24]), "+f"(d[25]), "+f"(d[26]), "+f"(d[27]), "+f"(d[28]), "+f"(d[29]), "+f"(d[30]), "+f"(d[31]),
        "+f"(d[32]), "+f"(d[33]), "+f"(d[34]), "+f"(d[35]), "+f"(d[36]), "+f"(d[37]), "+f"(d[38]), "+f"(d[39]),
        "+f"(d[40]), "+f"(d[41]), "+f"(d[42]), "+f"(d[43]), "+f"(d[44]), "+f"(d[45]), "+f"(d[46]), "+f"(d[47]),
        "+f"(d[48]), "+f"(d[49]), "+f"(d[50]), "+f"(d[51]), "+f"(d[52]), "+f"(d[53]), "+f"(d[54]), "+f"(d[55]),
        "+f"(d[56]), "+f"(d[57]), "+f"(d[58]), "+f"(d[59]), "+f"(d[60]), "+f"(d[61]), "+f"(d[62]), "+f"(d[63]),
        "+f"(d[64]), "+f"(d[65]), "+f"(d[66]), "+f"(d[67]), "+f"(d[68]), "+f"(d[69]), "+f"(d[70]), "+f"(d[71]),
        "+f"(d[72]), "+f"(d[73]), "+f"(d[74]), "+f"(d[75]), "+f"(d[76]), "+f"(d[77]), "+f"(d[78]), "+f"(d[79]),
        "+f"(d[80]), "+f"(d[81]), "+f"(d[82]), "+f"(d[83]), "+f"(d[84]), "+f"(d[85]), "+f"(d[86]), "+f"(d[87]),
        "+f"(d[88]), "+f"(d[89]), "+f"(d[90]), "+f"(d[91]), "+f"(d[92]), "+f"(d[93]), "+f"(d[94]), "+f"(d[95]),
        "+f"(e[0]), "+f"(e[1]), "+f"(e[2]), "+f"(e[3]), "+f"(e[4]), "+f"(e[5]), "+f"(e[6]), "+f"(e[7]),
        "+f"(e[8]), "+f"(e[9]), "+f"(e[10]), "+f"(e[11]), "+f"(e[12]), "+f"(e[13]), "+f"(e[14]), "+f"(e[15]),
        "+f"(e[16]), "+f"(e[17]), "+f"(e[18]), "+f"(e[19]), "+f"(e[20]), "+f"(e[21]), "+f"(e[22]), "+f"(e[23]),
        "+f"(e[24]), "+f"(e[25]), "+f"(e[26]), "+f"(e[27]), "+f"(e[28]), "+f"(e[29]), "+f"(e[30]), "+f"(e[31])
      : "l"(descA), "l"(descB), "r"(scaleD), "n"(TB));
}
template <int TB = 1>
__device__ __forceinline__ void wgmma_ss_n192(float (&d)[96], uint64_t descA, uint64_t descB, int scaleD) {
  asm volatile("{\n.reg .pred p;\nsetp.ne.b32 p, %98, 0;\n"
      "wgmma.mma_async.sync.aligned.m64n192k16.f32.bf16.bf16 {"
      "%0, %1, %2, %3, %4, %5, %6, %7, %8, %9, %10, %11, %12, %13, %14, %15,"
      "%16, %17, %18, %19, %20, %21, %22, %23, %24, %25, %26, %27, %28, %29, %30, %31,"
      "%32, %33, %34, %35, %36, %37, %38, %39, %40, %41, %42, %43, %44, %45, %46, %47,"
      "%48, %49, %50, %51, %52, %53, %54, %55, %56, %57, %58, %59, %60, %61, %62, %63,"
      "%64, %65, %66, %67, %68, %69, %70, %71, %72, %73, %74, %75, %76, %77, %78, %79,"
      "%80, %81, %82, %83, %84, %85, %86, %87, %88, %89, %90, %91, %92, %93, %94, %95"
      "}, %96, %97, p, 1, 1, 0, %99;\n}\n"
      : "+f"(d[0]), "+f"(d[1]), "+f"(d[2]), "+f"(d[3]), "+f"(d[4]), "+f"(d[5]), "+f"(d[6]), "+f"(d[7]),
        "+f"(d[8]), "+f"(d[9]), "+f"(d[10]), "+f"(d[11]), "+f"(d[12]), "+f"(d[13]), "+f"(d[14]), "+f"(d[15]),
        "+f"(d[16]), "+f"(d[17]), "+f"(d[18]), "+f"(d[19]), "+f"(d[20]), "+f"(d[21]), "+f"(d[22]), "+f"(d[23]),
        "+f"(d[24]), "+f"(d[25]), "+f"(d[26]), "+f"(d[27]), "+f"(d[28]), "+f"(d[29]), "+f"(d[30]), "+f"(d[31]),
        "+f"(d[32]), "+f"(d[33]), "+f"(d[34]), "+f"(d[35]), "+f"(d[36]), "+f"(d[37]), "+f"(d[38]), "+f"(d[39]),
        "+f"(d[40]), "+f"(d[41]), "+f"(d[42]), "+f"(d[43]), "+f"(d[44]), "+f"(d[45]), "+f"(d[46]), "+f"(d[47]),
        "+f"(d[48]), "+f"(d[49]), "+f"(d[50]), "+f"(d[51]), "+f"(d[52]), "+f"(d[53]), "+f"(d[54]), "+f"(d[55]),
        "+f"(d[56]), "+f"(d[57]), "+f"(d[58]), "+f"(d[59]), "+f"(d[60]), "+f"(d[61]), "+f"(d[62]), "+f"(d[63]),
        "+f"(d[64]), "+f"(d[65]), "+f"(d[66]), "+f"(d[67]), "+f"(d[68]), "+f"(d[69]), "+f"(d[70]), "+f"(d[71]),
        "+f"(d[72]), "+f"(d[73]), "+f"(d[74]), "+f"(d[75]), "+f"(d[76]), "+f"(d[77]), "+f"(d[78]), "+f"(d[79]),
        "+f"(d[80]), "+f"(d[81]), "+f"(d[82]), "+f"(d[83]), "+f"(d[84]), "+f"(d[85]), "+f"(d[86]), "+f"(d[87]),
        "+f"(d[88]), "+f"(d[89]), "+f"(d[90]), "+f"(d[91]), "+f"(d[92]), "+f"(d[93]), "+f"(d[94]), "+f"(d[95])
      : "l"(descA), "l"(descB), "r"(scaleD), "n"(TB));
}
template <unsigned long long DESC, int SCALE>
__device__ __forceinline__ void wgmma_rs_n56(float (&d)[28], uint32_t a0, uint32_t a1, uint32_t a2, uint32_t a3) {
  asm volatile("{\n.reg .b64 desc;\nmov.b64 desc, %32;\n"
      "wgmma.mma_async.sync.aligned.m64n56k16.f32.bf16.bf16 {"
      "%0, %1, %2, %3, %4, %5, %6, %7, %8, %9, %10, %11, %12, %13, %14, %15,"
      "%16, %17, %18, %19, %20, %21, %22, %23, %24, %25, %26, %27"
      "}, {%28, %29, %30, %31}, desc, %33, 1, 1, 0;\n}\n"
      : "+f"(d[0]), "+f"(d[1]), "+f"(d[2]), "+f"(d[3]), "+f"(d[4]), "+f"(d[5]), "+f"(d[6]), "+f"(d[7]),
        "+f"(d[8]), "+f"(d[9]), "+f"(d[10]), "+f"(d[11]), "+f"(d[12]), "+f"(d[13]), "+f"(d[14]), "+f"(d[15]),
        "+f"(d[16]), "+f"(d[17]), "+f"(d[18]), "+f"(d[19]), "+f"(d[20]), "+f"(d[21]), "+f"(d[22]), "+f"(d[23]),
        "+f"(d[24]), "+f"(d[25]), "+f"(d[26]), "+f"(d[27])
      : "r"(a0), "r"(a1), "r"(a2), "r"(a3), "n"(DESC), "n"(SCALE));
}
template <unsigned long long DESC, int SCALE>
__device__ __forceinline__ void wgmma_rs_n32(float (&d)[28], uint32_t a0, uint32_t a1, uint32_t a2, uint32_t a3) {
  asm volatile("{\n.reg .b64 desc;\nmov.b64 desc, %20;\n"
      "wgmma.mma_async.sync.aligned.m64n32k16.f32.bf16.bf16 {"
      "%0, %1, %2, %3, %4, %5, %6, %7, %8, %9, %10, %11, %12, %13, %14, %15"
      "}, {%16, %17, %18, %19}, desc, %21, 1, 1, 0;\n}\n"
      : "+f"(d[0]), "+f"(d[1]), "+f"(d[2]), "+f"(d[3]), "+f"(d[4]), "+f"(d[5]), "+f"(d[6]), "+f"(d[7]),
        "+f"(d[8]), "+f"(d[9]), "+f"(d[10]), "+f"(d[11]), "+f"(d[12]), "+f"(d[13]), "+f"(d[14]), "+f"(d[15])
      : "r"(a0), "r"(a1), "r"(a2), "r"(a3), "n"(DESC), "n"(SCALE));
}

constexpr int NB = 4096, NF = 26, DIN = 1664;
constexpr int NGEMM = 128, NEXTRA = 4, GRID = NGEMM + NEXTRA;
constexpr int NR = 2;
constexpr int NC_WG0 = 16;
constexpr int WK = 1;
constexpr int OB = 5;
constexpr int AR = 3;
constexpr int GC = 8;
constexpr int HK = 3;
constexpr int PE0 = 14;
constexpr int WD = 2;
constexpr int GI = 3;
constexpr int PE1 = 6;
constexpr int PE2 = 12;
constexpr int PS2 = 11;
constexpr int PS = 6;
constexpr int RB = 4;
constexpr int NC_GEMM = 29, NBIG = 16 * NR, POOL = NGEMM * NC_GEMM, NC_EXTRA = (NB - POOL - NBIG) / NEXTRA;
static_assert((NR == 1 || NR == 2) && NC_WG0 == 16, "split");
constexpr int CW_MAIN = 22 * 1792, CW_LIN = 2 * 1024, CW_BYTES = CW_MAIN + CW_LIN;
constexpr int XSLOT = 4096;

constexpr int UNIT = 8192, FS = 18;
constexpr int U_W = 6, U_XB = 18, U_SP = 24;
constexpr int CW_CUT = 9;
constexpr int OFF_CW = 0, OFF_CW2 = 6 * UNIT, OFF_CWL = 9 * UNIT;
constexpr int OFF_PART = OFF_CWL + CW_LIN;
constexpr int CROW = 528;
constexpr int OFF_CIN = 2 * UNIT;
constexpr int OFF_GIDX = 26 * UNIT;
constexpr int OFF_TIDX = OFF_GIDX + 128 * NF * 4 - 8 * 64 * 4;
constexpr int OFF_CIDX = OFF_GIDX + 128 * NF * 4;
constexpr int OFF_EPI = OFF_CIDX + 30 * NF * 4;
constexpr int OFF_DNN = OFF_EPI + 128 * 16;
constexpr int OFF_BAR = OFF_DNN + 96 * 4;
constexpr int SMEM_BYTES = OFF_BAR + 64 * 8;
static_assert(CW_CUT * 1792 <= 2 * UNIT && (22 - CW_CUT) * 1792 <= 3 * UNIT && 30 * CROW <= 2 * UNIT, "smem");
constexpr uint32_t SMEM_BASE = 1024;
static_assert(SMEM_BYTES <= 232448, "smem");
static_assert(OFF_EPI % 16 == 0 && OFF_CIDX % 16 == 0 && OFF_BAR % 8 == 0, "align");
constexpr int XOFF_W3 = 0, XOFF_W2 = 35152, XOFF_W1 = 70304, XOFF_M = XOFF_W1 + 7 * 1392, XOFF_TAB = XOFF_M + 32 * 40 * 4, XOFF_S = XOFF_TAB + 3072,
              XOFF_SLOT = 10 * UNIT, XOFF_CIN0 = 2 * UNIT, XOFF_CIN1 = 18 * UNIT, XOFF_CIDX = 22 * UNIT;
static_assert(XOFF_S + 7 * 3152 <= 21 * UNIT && 46 * CROW <= 3 * UNIT, "smem");

constexpr int BAR_WIN = 2,
              BAR_CW = 3,
              BAR_DNN = 4,
              BAR_C0 = 5,
              BAR_CIDX = 7,
              BAR_FULL = 8,
              BAR_EV = 16,
              BAR_GIDX = 24,
              BAR_W0 = 25, BAR_W2 = 26,
              BAR_T = 27,
              BAR_GDONE = 28,
              BAR_PART = 29,
              BAR_CFULL = 32,
              BAR_POOL = BAR_CFULL + 28;
constexpr int EV_CW = 29, EV_CIN = 30, EV_SLOT = 31, EV_END = 33;
__device__ __forceinline__ uint32_t ev_bar(uint32_t bars, int e) { return bars + 8 * (BAR_EV + (e & 7)); }
__device__ __forceinline__ uint32_t ev_par(int e) { return (e >> 3) & 1; }
__host__ __device__ constexpr int b_x(int t) { return ((0xb2c1430bu >> (4 * t)) & 15) * 2; }
__host__ __device__ constexpr int b_w(int t) { return (0x0d0a120eu >> (8 * (t & 3))) & 31; }
__host__ __device__ constexpr int b_ws(int t) { return (t & 3) == 3 ? 4 : 1; }

struct Scratch {
  uint4 cw[CW_BYTES / 16];
  float part[8 * NB];
  unsigned dflag[16 * 8];
  unsigned epoch[GRID];
  unsigned place[16 * 8];
  unsigned foldflag;
};
__device__ __align__(128) Scratch g_scratch;
struct GPtr { Scratch* s; const uint4* tab; const uint4* jobs; uint32_t zero; };

__device__ __forceinline__ void wg_fence() { asm volatile("wgmma.fence.sync.aligned;" ::: "memory"); }
__device__ __forceinline__ void wg_commit() { asm volatile("wgmma.commit_group.sync.aligned;" ::: "memory"); }
template <int N> __device__ __forceinline__ void wg_wait() { asm volatile("wgmma.wait_group.sync.aligned %0;" ::"n"(N) : "memory"); }
__device__ __forceinline__ uint64_t mkdesc(uint32_t addr, uint32_t lbo, uint32_t sbo, uint32_t swz) {
  return (uint64_t)((addr & 0x3FFFF) >> 4) | ((uint64_t)(lbo >> 4) << 16) | ((uint64_t)(sbo >> 4) << 32) | ((uint64_t)swz << 62);
}
__device__ __forceinline__ bool elect1() {
  uint32_t p; asm volatile("{\n.reg .pred p;\nelect.sync _|p, 0xffffffff;\nselp.b32 %0, 1, 0, p;\n}" : "=r"(p)); return p;
}
__device__ __forceinline__ int fresh(int v) { asm volatile("" : "+r"(v)); return v; }
__device__ __forceinline__ void sched_fence() { asm volatile("pmevent 0;" ::: "memory"); }
__device__ __forceinline__ void mbar_init(uint32_t bar, uint32_t cnt) { asm volatile("mbarrier.init.shared::cta.b64 [%0], %1;" ::"r"(bar), "r"(cnt) : "memory"); }
__device__ __forceinline__ void mbar_arrive(uint32_t bar) { asm volatile("mbarrier.arrive.shared::cta.b64 _, [%0];" ::"r"(bar) : "memory"); }
__device__ __forceinline__ void mbar_arrive_cta(uint32_t bar, uint32_t cta) {
  asm volatile("{\n.reg .b32 r;\nmapa.shared::cluster.u32 r, %0, %1;\nmbarrier.arrive.shared::cluster.b64 _, [r];\n}" ::"r"(bar), "r"(cta) : "memory");
}
__device__ __forceinline__ void mbar_expect_tx(uint32_t bar, uint32_t bytes) { asm volatile("mbarrier.arrive.expect_tx.shared::cta.b64 _, [%0], %1;" ::"r"(bar), "r"(bytes) : "memory"); }
__device__ __forceinline__ void mbar_wait(uint32_t bar, uint32_t parity) {
  asm volatile("{\n.reg .pred p;\nLAB_WAIT:\nmbarrier.try_wait.parity.shared::cta.b64 p, [%0], %1;\n@!p bra LAB_WAIT;\n}" ::"r"(bar), "r"(parity) : "memory");
}
__device__ __forceinline__ void flag_wait(const unsigned* p, unsigned target, unsigned sleep_ns) {
  asm volatile("{\n.reg .pred p;\n.reg .u32 n, v;\nmov.u32 n, 0;\nLAB_WAIT:\n"
               "ld.acquire.gpu.global.u32 v, [%0];\n"
               "sub.u32 v, v, %1;\n"
               "setp.ge.s32 p, v, 0;\n"
               "@p bra DONE;\n"
               "nanosleep.u32 %2;\n"
               "add.u32 n, n, 1;\n"
               "setp.lt.u32 p, n, 400000;\n"
               "@p bra LAB_WAIT;\n"
               "DONE:\n}" ::"l"(p), "r"(target), "r"(sleep_ns) : "memory");
}
__device__ __forceinline__ void flag_add(unsigned* p) { asm volatile("red.release.gpu.global.add.u32 [%0], 1;" ::"l"(p) : "memory"); }
__device__ __forceinline__ void tma_load(uint32_t dst, const CUtensorMap* tm, int c0, int c1, uint32_t bar) {
  asm volatile("cp.async.bulk.tensor.2d.shared::cluster.global.mbarrier::complete_tx::bytes [%0], [%1, {%3, %4}], [%2];"
               ::"r"(dst), "l"(tm), "r"(bar), "r"(c0), "r"(c1) : "memory");
}
__device__ __forceinline__ void tma_row_mc(uint32_t dst, const CUtensorMap* tm, int row, uint32_t bar) {
  asm volatile("cp.async.bulk.tensor.2d.shared::cluster.global.mbarrier::complete_tx::bytes.multicast::cluster [%0], [%1, {%3, %4}], [%2], %5;"
               ::"r"(dst), "l"(tm), "r"(bar), "r"(0), "r"(row), "h"((uint16_t)3));
}
__device__ __forceinline__ void tma_row(uint32_t dst, const CUtensorMap* tm, int row, uint32_t bar) {
  asm volatile("cp.async.bulk.tensor.2d.shared::cluster.global.mbarrier::complete_tx::bytes [%0], [%1, {%3, %4}], [%2];"
               ::"r"(dst), "l"(tm), "r"(bar), "r"(0), "r"(row));
}
__device__ __forceinline__ void bulk_load(uint32_t dst, const void* src, uint32_t bytes, uint32_t bar) {
  asm volatile("cp.async.bulk.shared::cluster.global.mbarrier::complete_tx::bytes [%0], [%1], %2, [%3];"
               ::"r"(dst), "l"(src), "r"(bytes), "r"(bar));
}
__device__ __forceinline__ void l2_prefetch(const void* src, uint32_t bytes) {
  asm volatile("cp.async.bulk.prefetch.L2.global [%0], %1;" ::"l"(src), "r"(bytes));
}
__device__ __forceinline__ void w_prefetch(const __nv_bfloat16* w1, int f, int cta, int piece) {
  l2_prefetch(w1 + (f * 64 + (cta >> 3) * 4 + (cta & 1) * 2 + (piece & 1)) * DIN + (piece < 2 ? (cta & 6) * 192 : 1536 + (cta & 4) * 16),
              piece < 2 ? 768 : 128);
}
__device__ __forceinline__ void cpasync16(uint32_t dst, const void* src) {
  asm volatile("cp.async.cg.shared.global [%0], [%1], 16;" ::"r"(dst), "l"(src) : "memory");
}
template <int ID, int N> __device__ __forceinline__ void bar_sync() { asm volatile("bar.sync %0, %1;" ::"n"(ID), "n"(N) : "memory"); }
template <int ID, int N> __device__ __forceinline__ void bar_arrive() { asm volatile("bar.arrive %0, %1;" ::"n"(ID), "n"(N) : "memory"); }
__device__ __forceinline__ void ldsm4t(uint32_t& a, uint32_t& b, uint32_t& c, uint32_t& d, uint32_t addr) {
  asm volatile("ldmatrix.sync.aligned.m8n8.x4.trans.shared.b16 {%0,%1,%2,%3}, [%4];" : "=r"(a), "=r"(b), "=r"(c), "=r"(d) : "r"(addr) : "memory");
}
__device__ __forceinline__ void ldsm2t(uint32_t& a, uint32_t& b, uint32_t addr) {
  asm volatile("ldmatrix.sync.aligned.m8n8.x2.trans.shared.b16 {%0,%1}, [%2];" : "=r"(a), "=r"(b) : "r"(addr) : "memory");
}
__device__ __forceinline__ int lds32(uint32_t addr) { int v; asm volatile("ld.shared.b32 %0, [%1];" : "=r"(v) : "r"(addr)); return v; }
__device__ __forceinline__ int2 lds64(uint32_t addr) { int2 v; asm volatile("ld.shared.v2.b32 {%0,%1}, [%2];" : "=r"(v.x), "=r"(v.y) : "r"(addr)); return v; }
__device__ __forceinline__ int4 lds128(uint32_t addr) {
  int4 v; asm volatile("ld.shared.v4.b32 {%0,%1,%2,%3}, [%4];" : "=r"(v.x), "=r"(v.y), "=r"(v.z), "=r"(v.w) : "r"(addr)); return v;
}
__device__ __forceinline__ float4 lds128f(uint32_t addr) {
  float4 v; asm volatile("ld.shared.v4.f32 {%0,%1,%2,%3}, [%4];" : "=f"(v.x), "=f"(v.y), "=f"(v.z), "=f"(v.w) : "r"(addr) : "memory"); return v;
}
__device__ __forceinline__ void sts32f(uint32_t addr, float v) { asm volatile("st.shared.f32 [%0], %1;" ::"r"(addr), "f"(v) : "memory"); }
__device__ __forceinline__ float bf_lo(uint32_t v) { return __uint_as_float(v << 16); }
__device__ __forceinline__ float bf_hi(uint32_t v) { return __uint_as_float(v & 0xffff0000u); }
__device__ __forceinline__ float bf2f(__nv_bfloat16 v) { return __bfloat162float(v); }

__device__ __forceinline__ uint32_t mul2(uint32_t a, uint32_t b) {
  uint32_t r; asm volatile("mul.rn.bf16x2 %0, %1, %2;" : "=r"(r) : "r"(a), "r"(b)); return r;
}
__device__ __forceinline__ uint32_t mul2lo(uint32_t a, uint32_t b) {
  uint32_t r;
  asm volatile("{\n.reg .b16 l, h;\n.reg .b32 t;\nmov.b32 {l, h}, %2;\nmov.b32 t, {l, l};\nmul.rn.bf16x2 %0, %1, t;\n}" : "=r"(r) : "r"(a), "r"(b));
  return r;
}
__device__ __forceinline__ uint32_t mul2hi(uint32_t a, uint32_t b) {
  uint32_t r;
  asm volatile("{\n.reg .b16 l, h;\n.reg .b32 t;\nmov.b32 {l, h}, %2;\nmov.b32 t, {h, h};\nmul.rn.bf16x2 %0, %1, t;\n}" : "=r"(r) : "r"(a), "r"(b));
  return r;
}

__host__ __device__ constexpr int xfield(int r, int e, int c) {
  return r == 9 ? 24 + e : 8 * (r / 3) + 2 * (((r % 3) + c) & 3) + (((r % 3) == 2 && c >= 2) ? 1 - e : e);
}
__host__ __device__ constexpr int blk_a(int b) { return b < 12 ? 3 * (b / 8) + ((b & 3) == 3) : (b < 15 ? 3 * (b - 12) : 3 * (b - 15)); }
__host__ __device__ constexpr int blk_b(int b) { return b < 12 ? 3 * (b < 4 ? 1 : 2) + ((b & 3) == 3 ? 0 : (b & 3)) : (b < 15 ? 3 * (b - 12) + 1 : 9); }
__host__ __device__ constexpr int slot_pq(int u, int e, int c) {
  return u < 36 ? (xfield(blk_a(u >> 1), e, c) | (xfield(blk_b(u >> 1), u & 1, c) << 8))
       : u < 39 ? (xfield(3 * (u - 36), e, c) | (xfield(3 * (u - 36), 0, c) << 8))
       : u < 42 ? (xfield(3 * (u - 39), e, c) | (xfield(3 * (u - 39) + 2, e, c) << 8))
       : u == 42 ? (xfield(3 * e, 1, c) * 257)
       : u == 43 ? (e == 0 ? (xfield(6, 1, c) * 257)
                           : (c == 0 ? 24 * 257 : c == 1 ? 25 * 257 : c == 2 ? (24 | 25 << 8) : 26 * 257))
       : u < 47 ? (xfield(3 * (u - 44), e, c) | (26 << 8))
       : (c == 0 ? ((24 + e) | 26 << 8) : c == 3 ? ((26 + e) | (27 - e) << 8) : 27 * 257);
}
struct SlotTab { uint32_t v[2 * 48 * 8]; };
constexpr SlotTab make_slot_tab() {
  SlotTab t{};
  for (int u = 0; u < 48; u++)
    for (int k = 0; k < 8; k++) {
      const int pq = slot_pq(u, k & 1, k >> 1), p = pq & 255, q = pq >> 8;
      t.v[u * 8 + k] = (uint32_t)((p * 28 + q) * 4) | ((uint32_t)(((p != q && q < 26) ? q * 28 + p : 27 * 28 + 27) * 4) << 16);
      t.v[384 + u * 8 + k] = (uint32_t)(q < 26 ? (p * 26 + q) * 2 : 1360) | ((uint32_t)((p != q && q < 26) ? (q * 26 + p) * 2 : 1360) << 16);
    }
  return t;
}
__device__ __align__(16) const SlotTab g_slot_tab = make_slot_tab();

struct CinCtx {
  uint32_t tab0, tab1, full, fmask, it, lim, co, sb;
  uint32_t cin, o03, o14, o25, o9, o78, selA, selB;
  bool ones, lead;
};
constexpr unsigned long long CW_DESC = (unsigned long long)((SMEM_BASE + OFF_CW) >> 4) | (8ull << 16) | (16ull << 32);
constexpr int OFF_INIT = U_SP * UNIT;
constexpr unsigned long long INIT_DESC = (unsigned long long)((SMEM_BASE + OFF_INIT) >> 4) | (9ull << 32);
constexpr unsigned long long ONES_DESC = (SMEM_BASE + OFF_INIT + 4608) >> 4;
constexpr unsigned long long CWL_DESC = CW_DESC + (OFF_CWL - OFF_CW) / 16;

template <int U>
__device__ __forceinline__ uint32_t zreg(uint32_t (&x)[11][2], int h, const CinCtx& c) {
  if constexpr (U < 36) {
    if constexpr (U & 1) return mul2hi(x[blk_a(U >> 1)][h], x[blk_b(U >> 1)][h]);
    else return mul2lo(x[blk_a(U >> 1)][h], x[blk_b(U >> 1)][h]);
  } else if constexpr (U < 39) {
    return mul2lo(x[3 * (U - 36)][h], x[3 * (U - 36)][h]);
  } else if constexpr (U < 42) {
    return mul2(x[3 * (U - 39)][h], x[3 * (U - 39) + 2][h]);
  } else if constexpr (U == 42) {
    const uint32_t p = __byte_perm(x[0][h], x[3][h], 0x7632);
    return mul2(p, p);
  } else {
    x[10][h] = c.ones ? 0x3f803f80u : x[9][h];
    return mul2(__byte_perm(x[6][h], x[10][h], c.selA), __byte_perm(x[6][h], x[10][h], c.selB));
  }
}

__host__ __device__ constexpr int kord(int s) { return s == 0 ? 21 : s < 4 ? 14 + s : s < 19 ? s - 4 : s - 1; }
template <int S0, int NS>
struct ZGroup {
  uint32_t z[NS][4];
  template <int I = 0>
  __device__ __forceinline__ void fill(uint32_t (&x)[11][2], const CinCtx& c) {
    if constexpr (I < NS) {
      z[I][0] = zreg<2 * kord(S0 + I)>(x, 0, c);
      z[I][1] = zreg<2 * kord(S0 + I)>(x, 1, c);
      z[I][2] = zreg<2 * kord(S0 + I) + 1>(x, 0, c);
      z[I][3] = zreg<2 * kord(S0 + I) + 1>(x, 1, c);
      fill<I + 1>(x, c);
    }
  }
  template <int I = 0>
  __device__ __forceinline__ void mma(float (&acc)[28]) {
    if constexpr (I < NS) {
      constexpr int S = kord(S0 + I);
      wgmma_rs_n56<CW_DESC + (S < CW_CUT ? S * 1792 : OFF_CW2 - OFF_CW + (S - CW_CUT) * 1792) / 16, (S0 + I) != 0>(acc, z[I][0], z[I][1], z[I][2], z[I][3]);
      mma<I + 1>(acc);
    }
  }
};

__device__ __forceinline__ void cin_finish(const CinCtx& c, float (&acc)[28], uint32_t out) {
#pragma unroll
  for (int i = 0; i < 28; i++) asm volatile("" : "+f"(acc[i]));
  float s0 = acc[12] * acc[13], s1 = acc[14] * acc[15];
#pragma unroll
  for (int i = 0; i < 12; i += 2) {
    s0 = fmaf(acc[i], acc[16 + i], s0);
    s1 = fmaf(acc[i + 1], acc[17 + i], s1);
  }
  sts32f(out, s0 + s1);
}

__device__ __forceinline__ void cin_ldsm(const CinCtx& c, uint32_t so, uint32_t (&x)[11][2], int i) {
  if (i == 0) ldsm4t(x[0][0], x[0][1], x[3][0], x[3][1], so + c.o03);
  if (i == 1) ldsm2t(x[6][0], x[6][1], so + c.o03 + 2048);
  if (i == 1) ldsm2t(x[9][0], x[9][1], so + c.o9 + 3072);
  if (i == 2) ldsm4t(x[1][0], x[1][1], x[4][0], x[4][1], so + c.o14);
  if (i == 3) ldsm4t(x[2][0], x[2][1], x[5][0], x[5][1], so + c.o25);
  if (i == 4) ldsm4t(x[7][0], x[7][1], x[8][0], x[8][1], so + c.o78 + 2048);
}
__device__ __forceinline__ bool cin_late(const CinCtx& c, int k) {
  uint32_t ok = 1;
  asm volatile("{\n.reg .pred p;\nmbarrier.test_wait.parity.shared::cta.b64 p, [%1], %2;\nselp.b32 %0, 1, 0, p;\n}"
               : "=r"(ok) : "r"(c.full + (c.it & c.fmask) + 8 * k), "r"((((c.it & ~c.fmask) << 25) ^ (c.lim - 9 - 8 * k - c.it)) >> 31) : "memory");
  return !ok;
}
__device__ __forceinline__ void cin_load(const CinCtx& c, int k, bool late, uint32_t (&x)[11][2]) {
  const uint32_t fb = c.full + (c.it & c.fmask) + 8 * k;
  if (__builtin_expect(late, 0)) mbar_wait(fb, ((c.it & ~c.fmask) >> 6) & 1);
#pragma unroll
  for (int i = 0; i < 5; i++) cin_ldsm(c, c.sb + (c.tab0 & 31) * UNIT + k * XSLOT, x, i);
  if (c.lead) mbar_arrive(fb + 64);
}
__device__ __forceinline__ void cin_advance(CinCtx& c) {
  const uint32_t t = __funnelshift_r(c.tab0, c.tab1, 8);
  c.tab1 = __funnelshift_r(c.tab1, c.tab0, 8);
  c.tab0 = t;
  c.it += 16;
  c.co += 2 * CROW;
}
constexpr int CG_SIZE = 2;
constexpr int CG_WAIT = 4;
constexpr int CG_HEAD = 4;
constexpr int CG_LOAD = 4;
constexpr int CG_N = (22 + CG_SIZE - 1) / CG_SIZE;
constexpr int CG_ASK = 4;
constexpr int CG_HW = 3;
template <int G, int GEND>
__device__ __forceinline__ void cin_groups(const CinCtx& c, uint32_t (&x)[11][2], float (&acc)[28],
                                           int q, bool& late, uint32_t (&xn)[11][2]) {
  if constexpr (G < GEND) {
    constexpr int S0 = G * CG_SIZE, NS = (S0 + CG_SIZE <= 22) ? CG_SIZE : 22 - S0;
    if constexpr (G == CG_ASK) late = cin_late(c, q);
    ZGroup<S0, NS> g; g.fill(x, c);
    wg_fence();
    g.mma(acc);
    wg_commit();
    if constexpr (G == CG_N - 1) {
      wg_fence();
      wgmma_rs_n32<CWL_DESC, 1>(acc, x[0][0], x[0][1], x[3][0], x[3][1]);
      wgmma_rs_n32<CWL_DESC + 1024 / 16, 1>(acc, x[6][0], x[6][1], x[10][0], x[10][1]);
      wg_commit();
    }
    if constexpr (G == CG_LOAD) cin_load(c, q, late, xn);
    if constexpr (G != CG_HEAD - 1) {
      if constexpr (G == CG_N - 1 || G < CG_HW) wg_wait<CG_WAIT + 1>(); else wg_wait<CG_WAIT>();
    }
    cin_groups<G + 1, GEND>(c, x, acc, q, late, xn);
  }
}
__device__ __forceinline__ void cin_head(const CinCtx& c, uint32_t (&x)[11][2], float (&acc)[28], int q, bool& late) {
  cin_groups<0, CG_HEAD>(c, x, acc, q, late, x);
}
__device__ __forceinline__ void cin_tail(const CinCtx& c, uint32_t (&x)[11][2], float (&acc)[28],
                                         int q, bool& late, uint32_t (&xn)[11][2]) {
  cin_groups<CG_HEAD, CG_N>(c, x, acc, q, late, xn);
}

__device__ __forceinline__ void cin_setup(CinCtx& c, uint32_t sb, int wg, int tid, bool gemm, int nj) {
  c.tab0 = !gemm ? 0x0d0c0b0a + wg * 0x04040404 : wg ? 0x0d0c0b0a : 0x100f0e1a;
  c.tab1 = !gemm ? c.tab0 : wg ? 0x17171615 : 0x14131211;
  c.full = sb + OFF_BAR + 8 * (BAR_CFULL + wg * 16);
  c.fmask = gemm ? 0x70 : 0x30;
  c.it = 0; c.lim = 8 * nj; c.sb = sb;
  c.lead = (tid & 31) == 0 && !gemm;
  const uint32_t f0 = tid & 7, ch = (tid & 0x60) | ((tid & 8) << 1), chm = ch | ((tid & 16) << 6);
  c.o03 = (f0 * 144) ^ chm;
  c.o14 = (((f0 + 2) & 7) * 144) ^ chm;
  c.o25 = c.o03 ^ (tid & 4 ? 5 * 144 : 4 * 144);
  c.o9 = ((tid & 1) * 144) ^ ch;
  c.o78 = tid & 16 ? c.o25 - 1024 : c.o14;
  const int q = tid & 3;
  c.selA = q == 1 ? 0x7632 : 0x5432;
  c.selB = q == 0 ? 0x5432 : 0x7632;
  c.ones = q == 3;
}
template <typename F0, typename F, typename F2>
__device__ __forceinline__ void cin_run(CinCtx& c, F0 first_load, F after_start, F2 before_end) {
  float accA[28], accB[28];
  uint32_t xA[11][2], xB[11][2];
  first_load(xA);
  bool late;
  cin_head(c, xA, accA, 0, late);
  after_start();
#pragma unroll 1
  for (;;) {
    const uint32_t out = c.cin + c.co;
    cin_tail(c, xA, accA, 0, late, xB);
    if (c.it + 8 >= c.lim) { before_end(false); wg_wait<0>(); cin_finish(c, accA, out); break; }
    cin_head(c, xB, accB, 1, late);
    wg_wait<CG_HEAD>();
    cin_finish(c, accA, out);
    cin_tail(c, xB, accB, 1, late, xA);
    cin_advance(c);
    if (c.it >= c.lim) { before_end(true); wg_wait<0>(); cin_finish(c, accB, out + CROW); break; }
    cin_head(c, xA, accA, 0, late);
    wg_wait<CG_HEAD>();
    cin_finish(c, accB, out + CROW);
  }
}

constexpr float ALPHA = 0.3292034911525734f, KAPPA = 2.423681954311584f;

constexpr int GD = 1;
constexpr int GK = 0;
constexpr int TK = 2;
constexpr int GL = 2;
template <int NG>
struct Gelu {
  float4 q[NG / 2];
  float u[4 * NG];
  float ab;
  uint32_t ep;
  static constexpr int END = NG + GD + 4;
  __device__ __forceinline__ void start(uint32_t a, uint32_t sb) {
    ep = a;
    ab = __int_as_float(lds32(sb + OFF_EPI + 1024));
  }
  __device__ __forceinline__ void take(const Gelu& o) {
#pragma unroll
    for (int m = TK; m < NG / 2; m++)
      asm volatile("mov.b32 %0, %4;\nmov.b32 %1, %5;\nmov.b32 %2, %6;\nmov.b32 %3, %7;"
                   : "=f"(q[m].x), "=f"(q[m].y), "=f"(q[m].z), "=f"(q[m].w) : "f"(o.q[m].x), "f"(o.q[m].y), "f"(o.q[m].z), "f"(o.q[m].w));
    ab = o.ab;
  }
  struct Nop { __device__ __forceinline__ void operator()(int) const {} };
  template <int I0, int I1, bool LOAD = true, typename F = Nop>
  __device__ __forceinline__ void part(float (&d)[4 * NG], float& r0, float& r1, F hook = F()) {
#pragma unroll
    for (int i = I0; i < I1; i++) {
      sched_fence();
      hook(i - I0);
#pragma unroll
      for (int m = 0; m < NG / 2; m++)
        if ((LOAD || m < TK) && i == 2 * m + GD + 4 - (m < 2 ? 2 : GL)) q[m] = lds128f(ep + m * 64);
#pragma unroll
      for (int e = 0; e < 4; e++) {
        const int k0 = 4 * i + e, k1 = k0 - 4, k2 = k0 - 8, k3 = k0 - 12, k4 = k3 - 4 * GD, k5 = k4 - 4;
        if (k3 >= 0 && k3 < 4 * NG) asm volatile("tanh.approx.f32 %0, %0;" : "+f"(u[k3]));
        if (k5 >= 0) {
          const float4 v = q[k5 >> 3];
          float& r = e & 2 ? r1 : r0;
          asm volatile("fma.rn.f32 %0, %1, %2, %0;" : "+f"(r) : "f"(d[k5]), "f"(k5 & 4 ? (e & 1 ? v.w : v.z) : (e & 1 ? v.y : v.x)));
        }
        if (k4 >= 0 && k4 < 4 * NG) asm volatile("fma.rn.f32 %0, %0, %1, %0;" : "+f"(d[k4]) : "f"(u[k4]));
        if (k2 >= 0 && k2 < 4 * NG) asm volatile("mul.rn.f32 %0, %0, %1;" : "+f"(u[k2]) : "f"(d[k2]));
        if (k1 >= 0 && k1 < 4 * NG) asm volatile("fma.rn.f32 %0, %1, %1, %2;" : "=f"(u[k1]) : "f"(d[k1]), "f"(KAPPA));
        if (k0 < 4 * NG) asm volatile("fma.rn.f32 %0, %0, %1, %2;" : "+f"(d[k0]) : "f"(ALPHA), "f"(ab));
      }
    }
    sched_fence();
  }
};
__device__ __forceinline__ void pin(float a, float b, uint32_t addr, uint32_t zero) {
  asm volatile("{\n.reg .pred p;\nsetp.ne.u32 p, %3, 0;\n@p st.shared.v2.f32 [%0], {%1, %2};\n}" ::"r"(addr), "f"(a), "f"(b), "r"(zero) : "memory");
}
__device__ __forceinline__ void hand_on(float (&d)[96], const float (&s)[96]) {
#pragma unroll
  for (int i = 0; i < 96; i++) asm volatile("mov.b32 %0, %1;" : "=f"(d[i]) : "f"(s[i]));
}
__device__ __forceinline__ uint64_t desc_x(int u) { return mkdesc(SMEM_BASE, 16, 1024, 1) + u * (UNIT / 16); }
__device__ __forceinline__ uint64_t desc_w(int u, int stride = 1) { return mkdesc(SMEM_BASE, stride * UNIT, 1024, 1) + u * (UNIT / 16); }
__device__ __forceinline__ void tile_step(float (&d)[96], uint64_t dA, uint64_t dB) {
  wg_fence();
#pragma unroll
  for (int k = 0; k < 4; k++) wgmma_ss_n192(d, dA + 2 * k, dB + 128 * k, 1);
  wg_commit();
}
template <int K0 = 0, int K1 = 4>
__device__ __forceinline__ void wide_step(float (&d)[96], float (&e)[32], uint64_t dA, uint64_t dB) {
  wg_fence();
#pragma unroll
  for (int k = K0; k < K1; k++) wgmma_ss_n256(d, e, dA + 2 * k, dB + 128 * k, 1);
  wg_commit();
}
constexpr int slot_of(int wg, int j) {
  return wg ? (j == 0 ? 24 * UNIT : j <= 8 ? 10 * UNIT + (j - 1) * XSLOT : 21 * UNIT + (j - 9) * XSLOT)
            : (j == 0 ? OFF_GIDX + 2 * XSLOT : (j < 3 ? OFF_GIDX + 2 * XSLOT : 14 * UNIT) + (j - 3) * XSLOT);
}
constexpr int NLW = 3;
constexpr int NE = 10;
constexpr int LB = 1;
struct alignas(8) Job { uint32_t wait, par, slot, full, idx, next; };
constexpr int OFF_WIN = OFF_EPI + 1028, OFF_JOB = OFF_EPI + 1040, OFF_PIDX = OFF_JOB + 32 * sizeof(Job), XOFF_JOB = 24 * UNIT, XOFF_DNN = 25 * UNIT;
static_assert(OFF_PIDX + 2 * NF * 4 <= OFF_DNN, "smem");
struct JobTab { Job v[2][32 + NC_EXTRA]; };
constexpr Job make_job(int rank, int wait, int par, int slot, int full, int idx, int next) {
  const uint32_t sb = SMEM_BASE + (rank << 24);
  return Job{sb + OFF_BAR + 8 * wait, uint32_t(par), sb + slot, sb + OFF_BAR + 8 * full, sb + idx, next ? sb + next : 0};
}
constexpr JobTab make_jobs() {
  JobTab t{};
  int m = 0;
  for (int n = 0; n < 36; n++) {
    const int wg = n < 7 ? n == 4 : n & 1, j = n < 4 ? n : n < 7 ? n - 1 - 3 * wg : wg ? n / 2 - 2 : n / 2 + 2, s = wg * NC_WG0 + j;
    if (s >= NC_GEMM + NR || j >= NC_WG0) continue;
    const int e = n < 7 ? EV_SLOT : EV_END;
    for (int odd = 0; odd < 2; odd++)
      t.v[odd][m] = make_job(odd, n < 3 ? BAR_GDONE : n < NE ? BAR_EV + (e & 7) : BAR_PART, n < 3 ? 0 : (e >> 3) & 1, s > NC_GEMM ? 25 * UNIT : slot_of(wg, j),
                                   s >= NC_GEMM ? BAR_POOL : j ? BAR_CFULL + wg * 16 + j - 1 : BAR_C0 + wg,
                                   s >= NC_GEMM ? OFF_PIDX + (s - NC_GEMM + (NR == 1 && odd)) * NF * 4 : OFF_CIDX + (s + odd) * NF * 4,
                             m + NLW < NC_GEMM + NR ? OFF_JOB + (m + NLW) * sizeof(Job) : 0);
    m++;
  }
  for (int n = 0; n < NC_EXTRA; n++) {
    const int wg = n & 1, j = n >> 1, bi = (j - 1) & 7;
    for (int odd = 0; odd < 2; odd++)
      t.v[odd][32 + n] = make_job(odd, j == 0 ? BAR_GDONE : j <= 8 ? BAR_EV + (EV_END & 7) : BAR_CFULL + wg * 16 + 8 + bi, j <= 8 ? 0 : (((j - 1) >> 3) & 1) ^ 1,
                           j ? XOFF_SLOT + (wg * 8 + bi) * XSLOT : OFF_GIDX + wg * XSLOT, j ? BAR_CFULL + wg * 16 + bi : BAR_C0 + wg,
                           XOFF_CIDX + (wg * NC_EXTRA / 2 + j) * NF * 4, n + 4 < NC_EXTRA ? XOFF_JOB + (n + 4) * sizeof(Job) : 0);
  }
  return t;
}
__device__ __align__(16) const JobTab g_jobs = make_jobs();
static_assert(((EV_END >> 3) & 1) == 0, "parity");

__device__ __forceinline__ int cin_start(int c) { return c < NGEMM ? c * NC_GEMM : NB - (GRID - c) * NC_EXTRA; }
__device__ __forceinline__ int group_of(int c) { return (c < 8 ? 4 + (c >> 1) : c < 72 ? (c - 8) >> 4 : (c - 16) / 14) * 2 + (c & 1); }

__device__ __forceinline__ int fold_i0(int e) { return e < 2 ? 7 * e : 2 + 6 * e; }
__device__ __forceinline__ uint32_t ldg16(const void* p) { uint16_t v; asm volatile("ld.global.nc.u16 %0, [%1];" : "=h"(v) : "l"(p)); return v; }
__device__ __forceinline__ uint32_t ldg32(const void* p) { uint32_t v; asm volatile("ld.global.nc.u32 %0, [%1];" : "=r"(v) : "l"(p)); return v; }
__device__ __forceinline__ uint4 ldg128(const void* p) {
  uint4 v; asm volatile("ld.global.nc.v4.u32 {%0,%1,%2,%3}, [%4];" : "=r"(v.x), "=r"(v.y), "=r"(v.z), "=r"(v.w) : "l"(p)); return v;
}
__device__ __forceinline__ void sts64f(uint32_t addr, float a, float b) { asm volatile("st.shared.v2.f32 [%0], {%1, %2};" ::"r"(addr), "f"(a), "f"(b) : "memory"); }
__device__ __forceinline__ float to_tf32(float v) { uint32_t r; asm("cvt.rna.tf32.f32 %0, %1;" : "=r"(r) : "f"(v)); return __uint_as_float(r); }
__device__ __forceinline__ float lds_bf(uint32_t addr) { uint16_t v; asm volatile("ld.shared.u16 %0, [%1];" : "=h"(v) : "r"(addr)); return __uint_as_float((uint32_t)v << 16); }
template <bool RAW>
__device__ __forceinline__ uint4 fold_chunk(uint32_t base, uint32_t tab) {
  const int4 t0 = lds128(tab), t1 = lds128(tab + 16);
  const uint32_t t[8] = {uint32_t(t0.x), uint32_t(t0.y), uint32_t(t0.z), uint32_t(t0.w), uint32_t(t1.x), uint32_t(t1.y), uint32_t(t1.z), uint32_t(t1.w)};
  float w[16];
#pragma unroll
  for (int k = 0; k < 16; k++) {
    const uint32_t a = base + (k & 1 ? t[k >> 1] >> 16 : t[k >> 1] & 0xffff);
    w[k] = RAW ? lds_bf(a) : __int_as_float(lds32(a));
  }
  uint32_t v[4];
#pragma unroll
  for (int c = 0; c < 4; c++) {
    __nv_bfloat162 pk = __floats2bfloat162_rn(w[4 * c] + w[4 * c + 1], w[4 * c + 2] + w[4 * c + 3]);
    v[c] = *reinterpret_cast<uint32_t*>(&pk);
  }
  return make_uint4(v[0], v[1], v[2], v[3]);
}
__device__ __forceinline__ int cw_chunk(int u, int n) {
  return ((u < 44 ? (u >> 1) * 1792 : CW_MAIN + ((u - 44) >> 1) * 1024) + (n >> 3) * 256 + (u & 1) * 128 + (n & 7) * 16) >> 4;
}
__device__ __forceinline__ float log2_sigma(uint32_t v, int n) {
  return __reduce_add_sync(0xffffffffu, (v & 0x7fff) + ((v >> 16) & 0x7fff)) * (1.f / (128 * n)) - 126.02f;
}
__device__ __forceinline__ uint32_t acc_offset(float lg, float cap) { return __float2int_rd(fminf(fmaxf(lg + 131.5f, 0.f), cap + 127.f)) << 7 | 0x2b; }
template <typename F>
__device__ __forceinline__ void fold_weights(F keep, int warp, uint32_t sb, int e, const __nv_bfloat16* __restrict__ wco,
                                             const __nv_bfloat16* __restrict__ ws, const __nv_bfloat16* __restrict__ table, const GPtr gp) {
  const int tid = threadIdx.x, lane = tid & 31;
  const uint32_t bars = sb + OFF_BAR;
  const uint32_t wc16 = ldg16(wco + (lane < NF ? 52 + lane : 0));
  sched_fence();
  const int i0 = fold_i0(e), ni = fold_i0(e + 1) - i0, i = i0 + warp;
  const bool own = warp < ni;
  const uint32_t wb16 = ldg16(wco + (lane < NF ? 26 + lane : 0)), wa16 = ldg16(wco + (lane < NF ? lane : 0));
  const uint32_t sx = ldg32(table + lane * 8), s2 = ldg32(ws + 17576 + lane * 8), s3 = ldg32(ws + 2 * 17576 + lane * 8);
  bar_sync<7, 288>();
  keep();
  const int ii = lane & 7, ic = i0 + ii;
  auto a_round = [&](int k) {
    const uint4 v = fold_chunk<true>(sb + XOFF_W1 + (ii < ni ? ii * 1392 + (ic & 1) * 8 : 0), sb + XOFF_TAB + 1536 + k * 128 + (lane >> 3) * 32);
    if (ii < ni && (k < 11 || ic >= 24)) gp.s->cw[cw_chunk(lane >> 3, ic < 24 ? 32 + ic : 2 * ic - 23) + k * 224 - (k == 11 ? (lane >> 4) * 48 : 0)] = v;
  };
  if (warp >= 6) {
    if (tid < 192 + 7) asm volatile("st.shared.v4.b32 [%0], {%1, %1, %1, %1};" ::"r"(sb + XOFF_W1 + (tid - 192) * 1392 + 1360), "r"(0) : "memory");
    sts64f(sb + XOFF_M + 26 * 160 + (tid - 192) * 8, 0.f, 0.f);
    if (tid < 256 - 8) sts64f(sb + XOFF_M + 26 * 160 + (tid - 128) * 8, 0.f, 0.f);
    if (tid < 192 + 48) gp.s->cw[cw_chunk(tid - 192, 28 + e)] = make_uint4(0, 0, 0, 0);
    if (tid < 192 + NF) {
      sts64f(sb + XOFF_M + lane * 160 + 104, bf_lo(wb16), 0.f);
      sts64f(sb + XOFF_M + lane * 160 + 112, 0.f, 0.f);
      sts64f(sb + XOFF_M + lane * 160 + 120, 0.f, 0.f);
    }
    if (warp == 7) {
      const float lx = log2_sigma(sx, 64) + 4.7f, l1 = log2_sigma(lane < NF ? wa16 : 0, NF), l2 = log2_sigma(lane < NF ? wb16 : 0, NF);
      const float l3 = log2_sigma(lane < NF ? wc16 : 0, NF) + log2_sigma(s3, 64) + lx;
      const float ct = bf_lo(acc_offset(fmaxf(l1, fmaxf(l2, l3) + log2_sigma(s2, 64) + lx), 100.f));
      const float w1i = __shfl_sync(0xffffffffu, bf_lo(wa16), ic);
      if (lane < 16 && ii < ni) sts64f(sb + XOFF_S + ii * 3152 + (26 + (lane >> 3)) * 112 + 104, lane < 8 ? ct : w1i, lane < 8 ? -ct : 0.f);
    }
    bar_sync<5, 64>();
    mbar_wait(bars + 8 * BAR_W0, 0);
    if (warp == 7) bar_arrive<4, 256>();
#pragma unroll 1
    for (int k = warp == 6 ? 0 : AR; k < (warp == 6 ? AR : 12); k++) a_round(k);
  } else {
    const uint32_t a = sb + XOFF_W3 + (tid < 169 ? tid : 0) * 8;
    const int o = tid * 2, o2 = o + 1;
    const uint32_t mo = sb + XOFF_M + (o / 13) * 160 + (o % 13) * 8, mo2 = sb + XOFF_M + (o2 / 13) * 160 + (o2 % 13) * 8;
    mbar_wait(bars + 8 * BAR_GIDX, 0);
    float m0 = 0.f, m1 = 0.f, m2 = 0.f, m3 = 0.f;
#pragma unroll 1
    for (int g0 = 0; g0 < NF; g0 += 13) {
      int2 v[13];
      float w[13];
#pragma unroll
      for (int g = 0; g < 13; g++) { v[g] = lds64(a + (g0 + g) * 1352); w[g] = __shfl_sync(0xffffffffu, bf_lo(wc16), g0 + g); }
#pragma unroll
      for (int g = 0; g < 13; g++) {
        m0 = fmaf(w[g], bf_lo(v[g].x), m0); m1 = fmaf(w[g], bf_hi(v[g].x), m1);
        m2 = fmaf(w[g], bf_lo(v[g].y), m2); m3 = fmaf(w[g], bf_hi(v[g].y), m3);
      }
    }
    if (tid < 169) {
      sts64f(mo, to_tf32(m0), to_tf32(m1));
      sts64f(mo2, to_tf32(m2), to_tf32(m3));
    }
  }
  if (warp < 7) {
  const uint32_t sT = sb + XOFF_S + (own ? warp : 0) * 3152;
  const int g = lane >> 2, c = lane & 3;
  uint32_t af[2][8];
  mbar_wait(bars + 8 * BAR_W2, 0);
#pragma unroll
  for (int k = 0; k < 8; k++) {
    const int h = 4 * k + c;
    const uint32_t a = sb + XOFF_W2 + ((h < NF ? h : 0) * 676 + (own ? i : 0) * 26 + 2 * g) * 2;
    af[0][k] = lds32(a);
    af[1][k] = lds32(a + (g < 5 ? 32 : 0));
  }
  bar_sync<4, 256>();
  if (own) {
    float d[4][2][4] = {};
#pragma unroll
    for (int ks = 0; ks < 4; ks++) {
#pragma unroll
      for (int n = 0; n < 4; n++) {
        const uint32_t b0 = lds32(sb + XOFF_M + (8 * ks + c) * 160 + (8 * n + g) * 4);
        const uint32_t b1 = lds32(sb + XOFF_M + (8 * ks + c + 4) * 160 + (8 * n + g) * 4);
#pragma unroll
        for (int m = 0; m < 2; m++)
          asm("mma.sync.aligned.m16n8k8.row.col.f32.tf32.tf32.f32 {%0,%1,%2,%3}, {%4,%5,%6,%7}, {%8,%9}, {%0,%1,%2,%3};"
              : "+f"(d[n][m][0]), "+f"(d[n][m][1]), "+f"(d[n][m][2]), "+f"(d[n][m][3])
              : "r"(af[m][2 * ks] << 16), "r"(af[m][2 * ks] & 0xffff0000u), "r"(af[m][2 * ks + 1] << 16),
                "r"(af[m][2 * ks + 1] & 0xffff0000u), "r"(b0), "r"(b1));
      }
    }
#pragma unroll
    for (int n = 0; n < 4; n++) {
      if (n < 3 || c < 2) {
        const uint32_t a = sT + 2 * g * 112 + (8 * n + 2 * c) * 4;
        sts64f(a, d[n][0][0], d[n][0][1]);
        sts64f(a + 112, d[n][0][2], d[n][0][3]);
        if (g < 5) {
          sts64f(a + 16 * 112, d[n][1][0], d[n][1][1]);
          sts64f(a + 17 * 112, d[n][1][2], d[n][1][3]);
        }
      }
    }
  }
  bar_sync<5, 224>();
#pragma unroll 1
  for (int k = warp; k < 12; k += 7) {
    const uint4 v = fold_chunk<false>(sb + XOFF_S + (ii < ni ? ii : 0) * 3152, sb + XOFF_TAB + k * 128 + (lane >> 3) * 32);
    if (ii < ni) gp.s->cw[cw_chunk(lane >> 3, ic < 24 ? ic : 2 * ic - 24) + k * 224 - (k == 11 ? (lane >> 4) * 48 : 0)] = v;
  }
  }
  __syncwarp();
  if (lane == 0) flag_add(&gp.s->foldflag);
  asm volatile("barrier.cluster.wait.acquire.aligned;" ::: "memory");
  bar_sync<4, 256>();
  if (tid >= 128 && tid < 132) mbar_arrive(ev_bar(bars, EV_END));
}

__global__ void __cluster_dims__(2, 1, 1) __launch_bounds__(384, 1)
xdeepfm_kernel(const int* __restrict__ idx, const __nv_bfloat16* __restrict__ table, const __nv_bfloat16* __restrict__ w1,
               const __nv_bfloat16* __restrict__ b1, const __nv_bfloat16* __restrict__ w2,
               const __nv_bfloat16* __restrict__ ws, const __nv_bfloat16* __restrict__ wco,
               const __nv_bfloat16* __restrict__ bout, __nv_bfloat16* __restrict__ out, const GPtr gp,
               const __grid_constant__ CUtensorMap tmW, const __grid_constant__ CUtensorMap tmT) {
  int myidx, idx1, idx2 = 0, idx3 = 0;
  {
    const int t = threadIdx.x, b = blockIdx.x, half = (b >> 1) ^ (t >= 256 ? t >> 4 : 0);
    const int* ip = idx + (((b >> 3) & 15) * 256 + (half & 1) * 128 + (t < 256 ? min(min(t >> 5, 4) * 4 + (t >> 5) * 16 + min(t & 31, 19), 127) : (b & 1) * 64 + ((t >> 1) & 48) + (t & 15))) * NF;
    asm volatile("{\n.reg .pred p;\nsetp.ge.u32 p, %5, 256;\nld.global.nc.v2.s32 {%0, %1}, [%4];\n@p ld.global.nc.v2.s32 {%2, %3}, [%4 + 8];\n}"
                 : "=r"(myidx), "=r"(idx1), "+r"(idx2), "+r"(idx3) : "l"(ip), "r"(t));
  }
  extern __shared__ __align__(1024) uint8_t smem[];
  const uint32_t sb = (uint32_t)__cvta_generic_to_shared(smem);
  const uint32_t bars = sb + OFF_BAR;
  const int tid = threadIdx.x, lane = tid & 31;
  const int warp = __shfl_sync(0xffffffffu, tid >> 5, 0);
  const int cta = blockIdx.x;
  const bool gemm = cta < NGEMM;
  const int nt = cta & 7, rank = cta & 1;

  uint32_t sx, sw;
  uint4 bv;
  asm volatile("{\n.reg .pred p;\nsetp.eq.u32 p, %9, 7;\n@p ld.global.nc.u32 %0, [%6];\n@p ld.global.nc.u32 %1, [%7];\n@p ld.global.nc.v4.u32 {%2, %3, %4, %5}, [%8];\n}"
               : "=r"(sx), "=r"(sw), "=r"(bv.x), "=r"(bv.y), "=r"(bv.z), "=r"(bv.w)
               : "l"(table + cta * 256 + lane * 8), "l"(w1 + nt * 192 + lane * 2),
                 "l"(b1 + (lane < 24 ? nt * 192 : 1536 - 192 + (nt >> 2) * 64) + lane * 8), "r"(tid >> 5));
  auto keep = [&]() {
    asm volatile("{\n.reg .pred p;\nsetp.ne.u32 p, %0, 0;\n@p st.shared.v2.b32 [%0], {%1, %2};\n@p st.shared.v2.b32 [%0 + 8], {%3, %4};\n"
                 "@p st.shared.b32 [%0 + 16], %5;\n@p st.shared.b32 [%0 + 24], %6;\n@p st.shared.v4.b32 [%0 + 32], {%7, %8, %9, %10};\n}"
                 ::"r"((uint32_t)(size_t)table & 1), "r"(myidx), "r"(idx1), "r"(idx2), "r"(idx3), "r"(sx), "r"(sw), "r"(bv.x), "r"(bv.y), "r"(bv.z), "r"(bv.w) : "memory");
  };
  if (warp == 8 && elect1()) {
    mbar_init(bars + 8 * BAR_GIDX, 1);
    mbar_init(bars + 8 * BAR_W2, 1);
    mbar_init(bars + 8 * BAR_W0, 1);
    asm volatile("fence.mbarrier_init.release.cluster;" ::: "memory");
    if (gemm) {
      mbar_expect_tx(bars + 8 * BAR_W0, 4 * UNIT);
#pragma unroll
      for (int i = 0; i < 4; i++)
        tma_load(sb + (U_W + i) * UNIT, &tmW, i < 3 ? nt * 192 + i * 64 : 1536 + (nt >> 2) * 64, 0, bars + 8 * BAR_W0);
    } else {
      mbar_expect_tx(bars + 8 * BAR_GIDX, 35152);
      bulk_load(sb + XOFF_W3, ws + 2 * 17576, 35152, bars + 8 * BAR_GIDX);
    }
  }
  if (warp == 8 && !gemm) bar_arrive<7, 288>();
  if (threadIdx.x < 256) {}
  else if (threadIdx.x >= 384 - 16) {
    const int l = threadIdx.x & 7;
    if (l < 7) asm volatile("prefetch.global.L2 [%0];" ::"l"(w1 + (((cta >> 3 & 15) * 2 + (cta & 1)) * 2 + ((threadIdx.x >> 3) & 1)) * DIN + (l < 6 ? (cta & 6) * 192 + l * 64 : 1536 + (cta & 4) * 16)));
  }
  else if (threadIdx.x >= 352 && threadIdx.x < 359) {
    const int l = blockIdx.x * 7 + threadIdx.x - 352;
    if (l < 824) asm volatile("prefetch.global.L2 [%0];" ::"l"(ws + (823 - l) * 64));
  }

  auto init = [&](int g) {
    if (elect1()) {
      if (g != 3) {
        const int n = g == 2 || (!gemm && g > 4 && (g & 1)) ? 4 : 1;
#pragma unroll
        for (int i = 0; i < 8; i++) mbar_init(bars + 64 * g + 8 * i, i == 4 && gemm && g == 7 ? NR : n);
      } else {
        mbar_init(bars + 8 * BAR_T, 2);
        mbar_init(bars + 8 * BAR_GDONE, 4);
        mbar_init(bars + 8 * BAR_PART, 8);
      }
      asm volatile("fence.mbarrier_init.release.cluster;" ::: "memory");
    }
  };
  if (warp >= 8) {
    const int pw = warp - 8;
    asm volatile("barrier.cluster.arrive.relaxed.aligned;" ::: "memory");
    if (elect1()) {
      if (gemm) {
        if (pw == 0) asm volatile("prefetch.tensormap [%0];" ::"l"(&tmT) : "memory");
        w_prefetch(w1, 1, cta, pw);
      } else if (pw == 0) {
        const int i0 = fold_i0(cta - NGEMM), ni = fold_i0(cta - NGEMM + 1) - i0;
        mbar_expect_tx(bars + 8 * BAR_W0, ni * 1360 + sizeof(SlotTab));
#pragma unroll 1
        for (int i = 0; i < ni; i++) bulk_load(sb + XOFF_W1 + i * 1392, ws + (((i0 + i) * 676) & ~7), 1360, bars + 8 * BAR_W0);
        bulk_load(sb + XOFF_TAB, gp.tab, sizeof(SlotTab), bars + 8 * BAR_W0);
        mbar_expect_tx(bars + 8 * BAR_W2, 35152);
        bulk_load(sb + XOFF_W2, ws + 17576, 35152, bars + 8 * BAR_W2);
      }
    }
    __syncwarp();
    asm volatile("setmaxnreg.dec.sync.aligned.u32 24;");
    asm volatile("barrier.cluster.wait.acquire.aligned;" ::: "memory");
    if (!gemm && elect1()) {
      mbar_arrive(bars + 8 * BAR_GDONE);
      if (pw == 3) {
        mbar_expect_tx(bars + 8 * BAR_CIDX, NC_EXTRA * (NF * 4 + sizeof(Job)));
        bulk_load(sb + XOFF_CIDX, idx + cin_start(cta) * NF, NC_EXTRA * NF * 4, bars + 8 * BAR_CIDX);
        bulk_load(sb + XOFF_JOB, gp.jobs + (32 + rank * (32 + NC_EXTRA)) * sizeof(Job) / 16, NC_EXTRA * sizeof(Job), bars + 8 * BAR_CIDX);
      }
    }
    __syncwarp();
    if (gemm) {
      {
        const uint32_t a = sb + OFF_GIDX + ((lane >> 4) * 64 + pw * 16 + (lane & 15)) * NF * 4;
        asm volatile("st.shared.v2.b32 [%0], {%1, %2};\nst.shared.v2.b32 [%0 + 8], {%3, %4};"
                     ::"r"(a), "r"(myidx), "r"(idx1), "r"(idx2), "r"(idx3) : "memory");
        keep();
        __syncwarp();
      }
      if (elect1()) {
        if (pw == 0) mbar_expect_tx(bars + 8 * BAR_FULL, 2 * UNIT);
#pragma unroll
        for (int j = 0; j < 16; j += 8) {
          int r[8];
#pragma unroll
          for (int i = 0; i < 8; i++) r[i] = lds32(sb + OFF_GIDX + ((64 + pw * 16 + j + i) * NF) * 4);
#pragma unroll
          for (int i = 0; i < 8; i++) tma_row_mc(sb + U_XB * UNIT + (rank * 64 + pw * 16 + j + i) * 128, &tmT, r[i], bars + 8 * BAR_FULL);
        }
        int s = 1;
#pragma unroll 1
        for (int fi = 1; fi < NF; fi++) {
          const int f = fresh(fi), pw = fresh(warp) - 8, ct = fresh(cta), nt = ct & 7;
          const int t = f - FS, st = t < 0 ? s : (t & 3) ^ ((t >> 1) & 1), e = f - 3 - (t > 1);
          const uint32_t fb = bars + 8 * (BAR_FULL + (f & 7)), ia = sb + OFF_GIDX + (pw * 16 * NF + f) * 4;
          const uint32_t d = sb + (st == 3 ? U_SP : 2 * st) * UNIT + ((ct & 1) * 64 + pw * 16) * 128;
          if (f == 4) mbar_wait(bars + 8 * BAR_GIDX, 0);
          int r[2][RB];
#pragma unroll
          for (int i = 0; i < RB; i++) r[0][i] = lds32(ia + i * NF * 4);
          if (e >= 0) mbar_wait(ev_bar(bars, e), ev_par(e));
          if (pw == 0) mbar_expect_tx(fb, t < 0 ? 8 * UNIT : 6 * UNIT);
#pragma unroll
          for (int j = 0; j < 16 / RB; j++) {
#pragma unroll
            for (int i = 0; i < RB; i++) r[(j + 1) & 1][i] = lds32(ia + (RB * j + RB + i + (RB * j + RB >= 16) * 48) * NF * 4);
#pragma unroll
            for (int i = 0; i < RB; i++) tma_row_mc(d + (RB * j + i) * 128, &tmT, r[j & 1][i], fb);
          }
          if (t < 0) {
#pragma unroll
            for (int j = 0; j < 16 / RB; j++) {
              if (j + 1 < 16 / RB) {
#pragma unroll
                for (int i = 0; i < RB; i++) r[(j + 1) & 1][i] = lds32(ia + (64 + RB * j + RB + i) * NF * 4);
              }
#pragma unroll
              for (int i = 0; i < RB; i++) tma_row_mc(d + U_XB * UNIT + (RB * j + i) * 128, &tmT, r[j & 1][i], fb);
            }
          }
          tma_load(sb + (U_W + 4 * st + pw) * UNIT, &tmW, pw < 3 ? nt * 192 + pw * 64 : 1536 + (nt >> 2) * 64, f * 64, fb);
          if (f == GI && pw < 2) {
            if (pw == 0) mbar_expect_tx(bars + 8 * BAR_GIDX, 128 * NF * 4);
            bulk_load(sb + OFF_GIDX + pw * 64 * NF * 4, idx + ((ct >> 3) * 256 + (((ct >> 1) ^ pw) & 1) * 128 + (ct & 1) * 64) * NF, 64 * NF * 4, bars + 8 * BAR_GIDX);
          }
          if (f == GC && pw == 2) {
            mbar_expect_tx(bars + 8 * BAR_CIDX, 32 * (NF * 4 + sizeof(Job)));
            bulk_load(sb + OFF_CIDX, idx + (ct * NC_GEMM & ~1) * NF, 30 * NF * 4, bars + 8 * BAR_CIDX);
            bulk_load(sb + OFF_PIDX, idx + (POOL + (group_of(ct) * NR & ~1)) * NF, 2 * NF * 4, bars + 8 * BAR_CIDX);
            bulk_load(sb + OFF_JOB, gp.jobs + (ct & 1) * ((32 + NC_EXTRA) * sizeof(Job) / 16), 32 * sizeof(Job), bars + 8 * BAR_CIDX);
          }
          if (f + WD < NF) w_prefetch(w1, f + WD, ct, pw);
          if (++s == 3) s = 0;
        }
        mbar_wait(bars + 8 * BAR_T, 0);
#pragma unroll 1
        for (int ti = 0; ti < 8; ti++) {
          const int t = fresh(ti), pw = fresh(warp) - 8, e = t < 4 ? 22 - !t : 19 + t;
          const uint32_t ia = sb + OFF_TIDX + t * 256 + pw * 64, fb = bars + 8 * (BAR_FULL + ((NF + t) & 7));
          const uint32_t d = sb + b_x(t) * UNIT + ((fresh(cta) & 1) * 64 + pw * 16) * 128;
          int4 r[2];
          r[0] = lds128(ia);
          r[1] = lds128(ia + 16);
          mbar_wait(ev_bar(bars, e), ev_par(e));
          if (pw == 0) mbar_expect_tx(fb, t < 3 ? 2 * UNIT : 5 * UNIT);
#pragma unroll
          for (int j = 0; j < 4; j++) {
            tma_row_mc(d + (4 * j + 0) * 128, &tmT, r[j & 1].x, fb);
            tma_row_mc(d + (4 * j + 1) * 128, &tmT, r[j & 1].y, fb);
            tma_row_mc(d + (4 * j + 2) * 128, &tmT, r[j & 1].z, fb);
            tma_row_mc(d + (4 * j + 3) * 128, &tmT, r[j & 1].w, fb);
            if (j < 2) r[j & 1] = lds128(ia + 32 + 16 * j);
          }
        }
        mbar_arrive(bars + 8 * BAR_GDONE);
      }
      __syncwarp();
    }
    {
    int cta; asm volatile("mov.u32 %0, %%ctaid.x;" : "=r"(cta));
    cta = __shfl_sync(0xffffffffu, cta, 0);
    const bool gemm = cta < NGEMM;
    const int bt = cta >> 3, nt = cta & 7;
    if (pw == 3) {
      if (elect1()) {
        if (!gemm)
          asm volatile("{\n.reg .pred p;\n.reg .u32 n, a, b, c, d;\nmov.u32 n, 0;\n"
                       "ld.relaxed.gpu.global.u32 a, [%0];\nnanosleep.u32 50;\nld.relaxed.gpu.global.u32 b, [%0];\nnanosleep.u32 50;\nld.relaxed.gpu.global.u32 c, [%0];\nnanosleep.u32 50;\n"
                       "LAB_WAIT:\n"
                       "ld.relaxed.gpu.global.u32 d, [%0];\nsetp.eq.u32 p, a, %1;\n@p bra DONE;\n"
                       "ld.relaxed.gpu.global.u32 a, [%0];\nsetp.eq.u32 p, b, %1;\n@p bra DONE;\n"
                       "ld.relaxed.gpu.global.u32 b, [%0];\nsetp.eq.u32 p, c, %1;\n@p bra DONE;\n"
                       "ld.relaxed.gpu.global.u32 c, [%0];\nsetp.eq.u32 p, d, %1;\n@p bra DONE;\n"
                       "add.u32 n, n, 1;\nsetp.lt.u32 p, n, 100000;\n@p bra LAB_WAIT;\n"
                       "DONE:\n}" ::"l"(&gp.s->foldflag), "r"((gp.s->epoch[fresh(cta)] + 1) * NEXTRA * 8) : "memory");
        asm volatile("fence.proxy.async.global;" ::: "memory");
        if (gemm) mbar_wait(ev_bar(bars, EV_CW), ev_par(EV_CW));
        mbar_expect_tx(bars + 8 * BAR_CW, CW_BYTES);
        bulk_load(sb + OFF_CW, gp.s->cw, CW_CUT * 1792, bars + 8 * BAR_CW);
        bulk_load(sb + OFF_CW2, gp.s->cw + CW_CUT * 1792 / 16, (22 - CW_CUT) * 1792, bars + 8 * BAR_CW);
        bulk_load(sb + OFF_CWL, gp.s->cw + CW_MAIN / 16, CW_LIN, bars + 8 * BAR_CW);
      }
      __syncwarp();
    }
    if (pw < NLW || !gemm) {
      if (elect1()) {
        const bool gemm = blockIdx.x < NGEMM;
        mbar_wait(bars + 8 * BAR_CIDX, 0);
#pragma unroll 1
        for (uint32_t o = sb + (gemm ? OFF_JOB : XOFF_JOB) + (warp - 8) * sizeof(Job); o;) {
          const int2 j0 = lds64(o), j1 = lds64(o + 8), j2 = lds64(o + 16);
          const uint32_t d = j1.x, cb = j1.y, ia = j2.x;
          o = j2.y;
          mbar_wait(j0.x, j0.y);
          mbar_expect_tx(cb, NF * 128);
#pragma unroll
          for (int k = 0; k < NF; k += 2 * LB) {
            int2 r[LB];
#pragma unroll
            for (int i = 0; i < LB; i++) if (k + 2 * i < NF) r[i] = lds64(ia + (k + 2 * i) * 4);
#pragma unroll
            for (int i = 0; i < LB; i++) if (k + 2 * i < NF) {
              tma_row(d + (k + 2 * i) * 128, &tmT, r[i].x, cb);
              tma_row(d + (k + 2 * i + 1) * 128, &tmT, r[i].y, cb);
            }
          }
        }
        if (gemm) mbar_wait(bars + 8 * BAR_POOL, 0);
      }
      __syncwarp();
    }
    if (pw == 3) {
      unsigned epoch;
      asm volatile("ld.global.u32 %0, [%1];" : "=r"(epoch) : "l"(gp.s->epoch + fresh(cta)));
      epoch++;
      const float bo = sb == SMEM_BASE + ((cta & 1) << 24) ? bf2f(bout[0]) : __int_as_float(0x7fc00000);
      if (gemm) {
        mbar_wait(bars + 8 * BAR_PART, 0);
        float4* dst = reinterpret_cast<float4*>(gp.s->part + nt * NB + bt * 256);
        dst[lane] = lds128f(sb + OFF_PART + lane * 16);
        dst[lane + 32] = lds128f(sb + OFF_PART + 512 + lane * 16);
        __syncwarp();
        if (lane == 0) flag_add(gp.s->dflag + (fresh(cta) >> 3) * 8);
      }
      const int c0 = cin_start(cta), ncin = gemm ? NC_GEMM : NC_EXTRA;
      flag_wait(gp.s->dflag + ((lane == 0 ? c0 : lane == 1 ? POOL : c0 + ncin - 1) >> 8) * 8, epoch * 8, 200);
      __syncwarp();
#pragma unroll 1
      for (int r = lane; r < ncin + gemm; r += 32) {
        const int b = r < ncin ? c0 + r : POOL + group_of(cta) * NR + (lds32(sb + OFF_WIN) & (NR - 1));
        float s = bo;
#pragma unroll
        for (int n = 0; n < 8; n++) s += __ldcg(gp.s->part + n * NB + b);
        sts64f(sb + (gemm ? OFF_DNN : XOFF_DNN) + r * 8, 0.125f * s, __int_as_float(b));
      }
      __syncwarp();
      if (lane == 0) { mbar_arrive(bars + 8 * BAR_DNN); gp.s->epoch[fresh(cta)] = epoch; }
    }
    }
  } else {
    const int wg = warp >> 2;
    const int p = tid & 127;
    init(warp);
    __syncwarp();
    asm volatile("barrier.cluster.arrive.relaxed.aligned;" ::: "memory");
    if (gemm) {
      if (warp == 7) {
        asm volatile("st.shared.b32 [%0], %1;" ::"r"(sb + OFF_INIT + 4608 + lane * 4), "r"(0x3f003f00) : "memory");
        const int lg = __reduce_add_sync(0xffffffffu, (sx & 0x7fff) + ((sx >> 16) & 0x7fff) + (sw & 0x7fff) + ((sw >> 16) & 0x7fff));
        const uint32_t co = (min(max((lg >> 6) - int((127 - 11.8 - OB) * 128), 0), (130 + OB) * 128) & 0x7f80) | 0x2b;
        const uint32_t bw[4] = {bv.x, bv.y, bv.z, bv.w};
#pragma unroll
        for (int i = 0; i < 8; i++)
          asm volatile("st.shared.v4.b32 [%0], {%1, %2, %2, %2};" ::"r"(sb + OFF_INIT + lane * 144 + i * 16), "r"(__byte_perm(bw[i >> 1], co, i & 1 ? 0x5432 : 0x5410)), "r"(0) : "memory");
        sts32f(sb + OFF_EPI + 1024, -ALPHA * __uint_as_float((co << 16) - 39));
        asm volatile("fence.proxy.async.shared::cta;" ::: "memory");
        bar_arrive<5, 160>();
      } else {
        const int row = min(warp, 4) * 4 + warp * 16 + (lane >> 3);
        const uint32_t a = sb + row * 128 + (((lane ^ row) & 7) << 4);
        const __nv_bfloat16* src = table + (lane & 7) * 8;
        const int l0 = ((fresh(a) >> 7) & 3) | (fresh((int)(size_t)src) & 1);
#pragma unroll
        for (int i = 0; i < 5; i++)
          asm volatile("{\n.reg .pred p;\n.reg .b32 r;\n.reg .b64 a;\nsetp.ne.b32 p, %4, 0;\nshfl.sync.idx.b32 r, %2, %3, 31, 0xffffffff;\n"
                       "mad.wide.s32 a, r, 128, %1;\n@p cp.async.cg.shared.global [%0], [a], 16;\n}"
                       ::"r"((a ^ (i & 1) * 64) + i * 512), "l"(src), "r"(myidx), "r"(4 * i + l0), "r"(int(i < 4 || warp < 4)) : "memory");
      }
      keep();
      asm volatile("barrier.cluster.wait.acquire.aligned;" ::: "memory");
    } else {
      fold_weights(keep, warp, sb, cta - NGEMM, wco, ws, table, gp);
    }
    asm volatile("setmaxnreg.inc.sync.aligned.u32 224;");
    float r0 = 0.f, r1 = 0.f, r2 = 0.f, r3 = 0.f;
    float d1[96];
    Gelu<24> g1;
    unsigned place = NR;
    const uint32_t ep = sb + OFF_EPI + (lane & 3) * 16;
    auto load_w = [&](int t) {
      const int w = warp & 3;
      if (w < 3 && elect1())
        tma_load(sb + (b_w(t) + b_ws(t) * w) * UNIT, &tmW, nt * 192 + w * 64, (NF - 1 - t) * 64, bars + 8 * (BAR_FULL + ((NF + t) & 7)));
    };
    int role; asm volatile("mov.u32 %0, %%ctaid.x;" : "=r"(role));
    role = role < NGEMM ? wg : 2;
    if (fresh(role) == 0) {
      asm volatile("setmaxnreg.inc.sync.aligned.u32 256;");
      float d0[96], dx[32], dw[96];
      Gelu<24> g0;
      bar_sync<5, 160>();
      wg_fence();
      wgmma_ss_n256<0>(dw, dx, ONES_DESC, INIT_DESC, 0);
      wgmma_ss_n192<0>(d0, ONES_DESC, INIT_DESC, 0);
      wg_commit();
      mbar_wait(bars + 8 * BAR_W0, 0);
      asm volatile("cp.async.wait_all;" ::: "memory");
      asm volatile("fence.proxy.async.shared::cta;" ::: "memory");
      bar_sync<2, 256>();
      const uint64_t dA0 = desc_x(rank), dA1 = desc_x(rank ^ 1);
      wg_fence();
#pragma unroll
      for (int k = 0; k < 4; k++) {
        wgmma_ss_n256(dw, dx, dA0 + 2 * k, desc_w(U_W) + 128 * k, 1);
        wgmma_ss_n192(d0, dA1 + 2 * k, desc_w(U_W) + 128 * k, 1);
      }
      wg_commit();
      constexpr unsigned long long STAGES = 0xb4b4924924924ull;
#pragma unroll 1
      for (int f = 1; f < NF - 3; f++) {
        mbar_wait(bars + 8 * (BAR_FULL + (f & 7)), (f >> 3) & 1);
        const int st = (STAGES >> (2 * f)) & 3, xo = (st == 3 ? U_SP : 2 * st) * (UNIT / 16);
        const uint64_t dB = desc_w(U_W + 4 * st);
        wg_fence();
        wgmma_ss_n256(dw, dx, dA0 + xo, dB, 1);
        wgmma_ss_n192(d0, dA1 + xo, dB, 1);
        wg_commit();
        wg_wait<1>();
        if (p < (f > FS ? 4 : 2)) mbar_arrive_cta(ev_bar(bars, f - 1), p & 1);
#pragma unroll
        for (int k = 1; k < 4; k++) {
          wgmma_ss_n256(dw, dx, dA0 + xo + 2 * k, dB + 128 * k, 1);
          wgmma_ss_n192(d0, dA1 + xo + 2 * k, dB + 128 * k, 1);
        }
        wg_commit();
      }
      {
        constexpr int x3 = 2 * (UNIT / 16), x4 = U_SP * (UNIT / 16), x5 = 4 * (UNIT / 16);
        const uint64_t dB3 = desc_w(U_W + 4), dB4 = desc_w(U_W + 12), dB5 = desc_w(U_W + 8);
        mbar_wait(bars + 8 * (BAR_FULL + 7), 0);
        tile_step(d0, dA1 + x3, dB3);
        wg_wait<1>();
        if (p < 4) mbar_arrive_cta(ev_bar(bars, NF - 4), p & 1);
        mbar_wait(bars + 8 * (BAR_FULL + 0), 1);
        tile_step(d0, dA1 + x4, dB4);
        if (WK) wide_step<0, WK>(dw, dx, dA0 + x3, dB3);
        mbar_wait(bars + 8 * (BAR_FULL + 1), 1);
        tile_step(d0, dA1 + x5, dB5);
        wide_step<WK, 4>(dw, dx, dA0 + x3, dB3);
        mbar_wait(bars + 8 * BAR_T, 0);
        g0.start(ep, sb);
        wg_wait<1>();
        wide_step(dw, dx, dA0 + x4, dB4);
        g0.part<0, PE1>(d0, r0, r1);
        wg_wait<1>();
        if (p < 4) mbar_arrive_cta(ev_bar(bars, NF - 3), p & 1);
        wide_step<0, HK>(dw, dx, dA0 + x5, dB5);
        g0.part<PE1, PE2>(d0, r0, r1);
        wg_wait<1>();
        bar_arrive<4, 256>();
        if (p < 4) mbar_arrive_cta(ev_bar(bars, NF - 2), p & 1);
        wide_step<HK, 4>(dw, dx, dA0 + x5, dB5);
        g0.part<PE2, PE0>(d0, r0, r1);
        wg_wait<0>();
        load_w(3);
        if (p < 4) mbar_arrive_cta(ev_bar(bars, NF - 1), p & 1);
      }
      g0.part<PE0, g0.END>(d0, r0, r1);
      Gelu<8> gx;
      gx.start(ep + 12 * 64, sb);
      gx.part<0, gx.END>(dx, r2, r3);
      hand_on(d1, dw);
      g1.take(g0);
      asm volatile("setmaxnreg.dec.sync.aligned.u32 224;");
    }
    if (fresh(role) == 1) {
      float d0[96], dw[96];
      bar_sync<3, 128>();
      wg_fence();
      wgmma_ss_n192<0>(d0, ONES_DESC, INIT_DESC, 0);
      wgmma_ss_n192<0>(dw, ONES_DESC + ((size_t)table & 1), INIT_DESC, 0);
      wg_commit();
      asm volatile("cp.async.wait_all;" ::: "memory");
      asm volatile("fence.proxy.async.shared::cta;" ::: "memory");
      bar_arrive<2, 256>();
      mbar_wait(bars + 8 * BAR_W0, 0);
      mbar_wait(bars + 8 * BAR_FULL, 0);
      wg_fence();
#pragma unroll
      for (int k = 0; k < 4; k++) {
        wgmma_ss_n192(d0, desc_x(U_XB) + 2 * k, desc_w(U_W) + 128 * k, 1);
        wgmma_ss_n192(dw, desc_x(U_XB + 1) + 2 * k, desc_w(U_W) + 128 * k, 1);
      }
      wg_commit();
      int s = 1;
#pragma unroll 1
      for (int f = 1; f < FS; f++) {
        mbar_wait(bars + 8 * (BAR_FULL + (f & 7)), (f >> 3) & 1);
        const uint64_t dA = desc_x(U_XB + 2 * s), dB = desc_w(U_W + 4 * s);
        wg_fence();
        wgmma_ss_n192(d0, dA, dB, 1);
        wgmma_ss_n192(dw, dA + 512, dB, 1);
        wg_commit();
        wg_wait<1>();
        if (p < 2) mbar_arrive_cta(ev_bar(bars, f - 1), p);
#pragma unroll
        for (int k = 1; k < 4; k++) {
          wgmma_ss_n192(d0, dA + 2 * k, dB + 128 * k, 1);
          wgmma_ss_n192(dw, dA + 512 + 2 * k, dB + 128 * k, 1);
        }
        wg_commit();
        if (++s == 3) s = 0;
      }
      wg_wait<0>();
      if (p < 2) mbar_arrive_cta(ev_bar(bars, FS - 1), p);
      {
        const uint32_t a = sb + OFF_GIDX + 64 * NF * 4;
        const uint32_t ww = ldg32(w2 + 2 * p + (p < 96 ? nt * 192 : 1536 - 192 + (nt >> 2) * 64));
        int v[4];
#pragma unroll
        for (int i = 0; i < 4; i++) v[i] = lds32(a + (((p & 15) * 4 + i) * NF + (NF - 1 - (p >> 4))) * 4);
        bar_sync<3, 128>();
        asm volatile("st.shared.v4.b32 [%0], {%1, %2, %3, %4};" ::"r"(sb + OFF_TIDX + p * 16), "r"(v[0]), "r"(v[1]), "r"(v[2]), "r"(v[3]) : "memory");
        sts64f(sb + OFF_EPI + (p >> 3) * 64 + (p & 3) * 16 + (p & 4) * 2, (0.5f / ALPHA) * bf_lo(ww), (0.5f / ALPHA) * bf_hi(ww));
        bar_sync<3, 128>();
        if (p < 2) {
          flag_wait(&gp.s->foldflag, (gp.s->epoch[cta] + 1) * NEXTRA * 8, 0);
          mbar_arrive(bars + 8 * BAR_T);
        }
        __syncwarp();
      }
      mbar_wait(ev_bar(bars, FS), ev_par(FS));
      unsigned* tp = gp.s->place + group_of(cta) * 8;
      asm volatile("" : "+l"(tp));
      sched_fence();
      mbar_wait(bars + 8 * (BAR_FULL + 2), 1);
      bar_sync<4, 256>();
#pragma unroll
      for (int t = 0; t < 4; t++) {
        if (t) mbar_wait(bars + 8 * (BAR_FULL + 2 + t), 1);
        const uint64_t dA = desc_x(b_x(t)), dB = desc_w(b_w(t), b_ws(t));
        wg_fence();
#pragma unroll
        for (int k = 0; k < 4; k++) {
          wgmma_ss_n192(d0, dA + 2 * k, dB + 128 * k, 1);
          wgmma_ss_n192(dw, dA + 512 + 2 * k, dB + 128 * k, 1);
          if (k == 1 && t) {
            wg_commit();
            wg_wait<1>();
            mbar_wait(ev_bar(bars, NF - 1), ev_par(NF - 1));
            load_w(3 + t);
            if (t == 1 && p < 4) mbar_arrive_cta(ev_bar(bars, 26), p & 1);
            if (t == 3)
              asm volatile("{\n.reg .pred p;\nsetp.eq.u32 p, %2, 0;\n@p st.shared.b32 [%1], %0;\n@p mbarrier.arrive.shared::cta.b64 _, [%3];\n}"
                           ::"r"(place), "r"(sb + OFF_WIN), "r"(p), "r"(bars + 8 * BAR_WIN) : "memory");
            wg_fence();
          }
        }
        wg_commit();
        if (t == 0)
          asm volatile("{\n.reg .pred p;\nsetp.eq.u32 p, %2, 0;\n@p atom.relaxed.gpu.global.inc.u32 %0, [%1], 7;\n}" : "+r"(place) : "l"(tp), "r"(p));
      }
      mbar_wait(bars + 8 * (BAR_FULL + 6), 1);
      tile_step(d0, desc_x(b_x(4)), desc_w(b_w(4)));
      wg_wait<1>();
      load_w(7);
      if (p < 4) mbar_arrive(ev_bar(bars, EV_CW));
      mbar_wait(bars + 8 * (BAR_FULL + 7), 1);
      tile_step(d0, desc_x(b_x(5)), desc_w(b_w(5)));
      mbar_wait(bars + 8 * (BAR_FULL + 0), 0);
      tile_step(d0, desc_x(b_x(6)), desc_w(b_w(6)));
      mbar_wait(bars + 8 * (BAR_FULL + 1), 0);
      tile_step(d0, desc_x(b_x(7)), desc_w(b_w(7), 4));
      tile_step(dw, desc_x(b_x(4) + 1), desc_w(b_w(4)));
      Gelu<24> g0;
      g0.start(ep, sb);
      mbar_wait(bars + 8 * BAR_WIN, 0);
      place = lds32(sb + OFF_WIN);
      wg_wait<1>();
      tile_step(dw, desc_x(b_x(5) + 1), desc_w(b_w(5)));
      g0.part<0, PS>(d0, r0, r1);
      wg_wait<1>();
      if (p < 4) mbar_arrive(ev_bar(bars, 30));
      tile_step(dw, desc_x(b_x(6) + 1), desc_w(b_w(6)));
      g0.part<PS, 2 * PS>(d0, r0, r1);
      wg_wait<1>();
      if (p < 4) mbar_arrive(ev_bar(bars, 31));
      tile_step(dw, desc_x(b_x(7) + 1), desc_w(b_w(7), 4));
      g0.part<2 * PS, 2 * PS + PS2>(d0, r0, r1);
      wg_wait<0>();
      if (p < 4) mbar_arrive(ev_bar(bars, EV_END));
      g0.part<2 * PS + PS2, g0.END>(d0, r0, r1);
      hand_on(d1, dw);
      g1.take(g0);
    }
    g1.ep = ep;
    if (fresh(role) < 2) g1.part<0, g1.END - GK, false>(d1, r2, r3);

    {
    int cta, tid;
    asm volatile("mov.u32 %0, %%ctaid.x;" : "=r"(cta));
    asm volatile("mov.u32 %0, %%tid.x;" : "=r"(tid));
    const bool gemm = role < 2;
    const int lane = tid & 31, p = tid & 127;
    const int rb = !wg ? 0 : gemm ? NC_WG0 : NC_EXTRA / 2;
    place = __shfl_sync(0xffffffffu, place, 0);
    const int nj = !gemm ? NC_EXTRA / 2 : wg ? NC_GEMM - NC_WG0 + (place < NR) : NC_WG0;
    const uint32_t cinb = sb + (gemm ? OFF_CIN + rb * CROW : wg ? XOFF_CIN1 : XOFF_CIN0);
    CinCtx c;
    cin_setup(c, sb, wg, tid, gemm, nj);
    if (place == 1 && NR == 2) c.tab1 += 0x20000;
    c.co = cinb;
    c.cin = p * 4;
    struct Res { uint32_t a, on; float dn; __nv_bfloat16* op; };
    int bar_id;
    auto prepare = [&](int r) {
      Res o;
      o.on = (p & 7) == 0 && r >= 0;
      r = max(r, 0);
      o.a = cinb + (p & 7) * 16 + r * CROW;
      const int2 v = lds64(sb + (gemm ? OFF_DNN : XOFF_DNN) + (rb + r) * 8);
      o.dn = __int_as_float(v.x);
      o.op = out + v.y;
      asm volatile("" : "+r"(o.a), "+r"(o.on), "+f"(o.dn), "+l"(o.op));
      return o;
    };
    auto sum = [&](const Res& o) {
      const float4 v0 = lds128f(o.a), v1 = lds128f(o.a + 128), v2 = lds128f(o.a + 256), v3 = lds128f(o.a + 384);
      float s = ((((v0.x + o.dn) + v0.y) + (v0.z + v0.w)) + ((v1.x + v1.y) + (v1.z + v1.w))) +
                (((v2.x + v2.y) + (v2.z + v2.w)) + ((v3.x + v3.y) + (v3.z + v3.w)));
      s += __shfl_xor_sync(0xffffffffu, s, 1);
      s += __shfl_xor_sync(0xffffffffu, s, 2);
      return s + __shfl_xor_sync(0xffffffffu, s, 4);
    };
    auto store = [&](const Res& o, float s) {
      asm volatile("{\n.reg .pred p;\n.reg .b16 v;\nsetp.ne.u32 p, %2, 0;\ncvt.rn.bf16.f32 v, %1;\n@p st.global.b16 [%0], v;\n}" ::"l"(o.op), "f"(s), "r"(o.on) : "memory");
    };
    Res last;
    cin_run(c, [&](uint32_t (&x)[11][2]) {
      mbar_wait(bars + 8 * (BAR_C0 + wg), 0);
      const uint32_t first = sb + (!gemm ? OFF_GIDX + wg * XSLOT : wg ? 24 * UNIT : OFF_GIDX + 2 * XSLOT);
      g1.part<g1.END - GK, g1.END, false>(d1, r2, r3, [&](int i) { cin_ldsm(c, first, x, i); });
#pragma unroll
      for (int i = GK; i < 5; i++) cin_ldsm(c, first, x, i);
      mbar_wait(bars + 8 * BAR_CW, 0);
    }, [&]() {
      sched_fence();
      const bool b0 = lane & 1, b1_ = lane & 2;
      float a = b0 ? r1 : r0, b = b0 ? r0 : r1, cc = b0 ? r3 : r2, d = b0 ? r2 : r3;
      a += __shfl_xor_sync(0xffffffffu, b, 1);
      cc += __shfl_xor_sync(0xffffffffu, d, 1);
      float e = b1_ ? cc : a, f = b1_ ? a : cc;
      e += __shfl_xor_sync(0xffffffffu, f, 2);
      const uint32_t row4 = (tid & 0x1c) | ((tid & 1) << 5) | ((tid & 0x60) << 1) | ((tid & 2) << 7);
      sts32f(sb + OFF_PART + (row4 ^ (((((cta >> 1) ^ wg) & 1) << 9) | ((~cta & ~wg & 1) << 8))), e);
      __syncwarp();
      if (lane == 0) mbar_arrive(bars + 8 * BAR_PART);
      mbar_wait(ev_bar(bars, gemm ? EV_CIN : EV_END), gemm);
    }, [&](bool even) {
      mbar_wait(bars + 8 * BAR_DNN, 0);
      static_assert(NC_EXTRA % 4 == 0, "even");
      if (even && !gemm) {
        asm volatile("bar.sync %0, 128;" ::"r"(1 + 2 * wg) : "memory");
        const Res o1 = prepare(NC_EXTRA / 2 - 32 + (p >> 3)), o2 = prepare(NC_EXTRA / 2 - 48 + (p >> 3));
        const float s1 = sum(o1), s2 = sum(o2);
        store(o1, s1);
        store(o2, s2);
      }
      last = prepare(nj - 16 + (p >> 3));
      bar_id = fresh(1 + (tid >> 6 & 2));
      sched_fence();
    });
    asm volatile("bar.sync %0, 128;" ::"r"(bar_id) : "memory");
    store(last, sum(last));
    }
  }
}

typedef CUresult (*EncodeFn)(CUtensorMap*, CUtensorMapDataType, cuuint32_t, void*, const cuuint64_t*, const cuuint64_t*,
                             const cuuint32_t*, const cuuint32_t*, CUtensorMapInterleave, CUtensorMapSwizzle,
                             CUtensorMapL2promotion, CUtensorMapFloatOOBfill);

extern "C" void kernel_launch(void* const* d_in, const int* in_sizes, int n_in, void* d_out, int out_size) {
  void* fn = nullptr;
  cudaDriverEntryPointQueryResult q;
  cudaGetDriverEntryPoint("cuTensorMapEncodeTiled", &fn, cudaEnableDefault, &q);
  EncodeFn enc = (EncodeFn)fn;
  CUtensorMap tmW, tmT;
  const cuuint32_t es[3] = {1, 1, 1};
  {
    cuuint64_t dims[2] = {DIN, DIN}, st[1] = {DIN * 2};
    cuuint32_t box[2] = {64, 64};
    enc(&tmW, CU_TENSOR_MAP_DATA_TYPE_BFLOAT16, 2, d_in[4], dims, st, box, es, CU_TENSOR_MAP_INTERLEAVE_NONE,
        CU_TENSOR_MAP_SWIZZLE_128B, CU_TENSOR_MAP_L2_PROMOTION_NONE, CU_TENSOR_MAP_FLOAT_OOB_FILL_NONE);
  }
  {
    cuuint64_t dims[2] = {64, (cuuint64_t)(in_sizes[1] / 64)}, st[1] = {128};
    cuuint32_t box[2] = {64, 1};
    enc(&tmT, CU_TENSOR_MAP_DATA_TYPE_BFLOAT16, 2, d_in[1], dims, st, box, es, CU_TENSOR_MAP_INTERLEAVE_NONE,
        CU_TENSOR_MAP_SWIZZLE_128B, CU_TENSOR_MAP_L2_PROMOTION_NONE, CU_TENSOR_MAP_FLOAT_OOB_FILL_NONE);
  }
  GPtr gp;
  gp.zero = 0;
  cudaGetSymbolAddress((void**)&gp.s, g_scratch);
  cudaGetSymbolAddress((void**)&gp.tab, g_slot_tab);
  cudaGetSymbolAddress((void**)&gp.jobs, g_jobs);
  cudaFuncSetAttribute(xdeepfm_kernel, cudaFuncAttributeMaxDynamicSharedMemorySize, SMEM_BYTES);
  xdeepfm_kernel<<<GRID, 384, SMEM_BYTES, cudaStreamPerThread>>>(
      (const int*)d_in[0], (const __nv_bfloat16*)d_in[1], (const __nv_bfloat16*)d_in[4], (const __nv_bfloat16*)d_in[5],
      (const __nv_bfloat16*)d_in[6], (const __nv_bfloat16*)d_in[2], (const __nv_bfloat16*)d_in[3],
      (const __nv_bfloat16*)d_in[7], (__nv_bfloat16*)d_out, gp, tmW, tmT);
}
```
